```python
import torch

def _softmax(x, axis=-1):
    return torch.softmax(x, dim=axis)
def _gelu(x):
    return torch.nn.functional.gelu(x, approximate="tanh")
def _silu(x):
    return torch.nn.functional.silu(x)
def _sigmoid(x):
    return torch.sigmoid(x)
def _layernorm(x, axis=-1, eps=1e-5):
    m = x.mean(dim=axis, keepdim=True)
    v = x.var(dim=axis, keepdim=True, unbiased=False)
    return (x - m) / torch.sqrt(v + eps)
def _scatter_add(tgt, idx, src, axis=0):
    return tgt.clone().index_add_(axis, idx, src)
def _segment_sum(src, seg, n):
    out = torch.zeros((n,) + src.shape[1:], dtype=src.dtype)
    return out.index_add_(0, seg, src)
def _pad(x, pw):
    flat = tuple(v for pair in reversed(pw) for v in pair)
    return torch.nn.functional.pad(x, flat)

kernel_name = 'concat_heads__mha_block_cached__mha_block_cached__near_ridge'

def setup_inputs():

    _w = (lambda a: (lambda t: t.to(torch.bfloat16) if t.is_floating_point() else t)(torch.as_tensor(a)))
    def _A_setup():
        B, Sq, D = 8, 304, 448
        H, Sk, Dh = 16, 1024, 256
        return {
            "x": _w((lambda *s: torch.randn(*s, dtype=torch.bfloat16) * 0.8)(B, Sq, D)),
            "k_cache": _w((lambda *s: torch.randn(*s, dtype=torch.bfloat16) * 0.8)(B, H, Sk, Dh)),
            "v_cache": _w((lambda *s: torch.randn(*s, dtype=torch.bfloat16) * 0.05)(B, H, Sk, Dh)),
            "wq": _w((lambda *s: torch.randn(*s, dtype=torch.bfloat16) * 0.8)(D, H * Dh) * (D ** -0.5)),
            "wo": _w((lambda *s: torch.randn(*s, dtype=torch.bfloat16) * 0.05)(H * Dh, D) * ((H * Dh) ** -0.5)),
        }
    _A_in = _A_setup()

    def _B_setup():
        B, Sq, D = 8, 304, 448
        H, Sk, Dh = 16, 1024, 256
        return {
            "x": _w((lambda *s: torch.randn(*s, dtype=torch.bfloat16) * 0.8)(B, Sq, D)),
            "k_cache": _w((lambda *s: torch.randn(*s, dtype=torch.bfloat16) * 0.8)(B, H, Sk, Dh)),
            "v_cache": _w((lambda *s: torch.randn(*s, dtype=torch.bfloat16) * 0.05)(B, H, Sk, Dh)),
            "wq": _w((lambda *s: torch.randn(*s, dtype=torch.bfloat16) * 0.8)(D, H * Dh) * (D ** -0.5)),
            "wo": _w((lambda *s: torch.randn(*s, dtype=torch.bfloat16) * 0.05)(H * Dh, D) * ((H * Dh) ** -0.5)),
        }
    _B_in = _B_setup()

    return {
        "A_x": _A_in["x"],
        "A_k_cache": _A_in["k_cache"],
        "A_v_cache": _A_in["v_cache"],
        "A_wq": _A_in["wq"],
        "A_wo": _A_in["wo"],
        "B_x": _B_in["x"],
        "B_k_cache": _B_in["k_cache"],
        "B_v_cache": _B_in["v_cache"],
        "B_wq": _B_in["wq"],
        "B_wo": _B_in["wo"],
    }

def reference(A_x, A_k_cache, A_v_cache, A_wq, A_wo, B_x, B_k_cache, B_v_cache, B_wq, B_wo):
    def _A_ref(x, k_cache, v_cache, wq, wo):
        B, Sq, D = x.shape
        H, Dh = 16, 256
        q = (lambda x, *d: x.permute(*d))((x @ wq).reshape(B, Sq, H, Dh), 0, 2, 1, 3)
        scores = torch.einsum("bhqd,bhkd->bhqk", q, k_cache) * (Dh ** -0.5)
        p = _softmax(scores, axis=-1)
        o = torch.einsum("bhqk,bhkd->bhqd", p, v_cache)
        return (lambda x, *d: x.permute(*d))(o, 0, 2, 1, 3).reshape(B, Sq, H * Dh) @ wo

    def _B_ref(x, k_cache, v_cache, wq, wo):
        B, Sq, D = x.shape
        H, Dh = 16, 256
        q = (lambda x, *d: x.permute(*d))((x @ wq).reshape(B, Sq, H, Dh), 0, 2, 1, 3)
        scores = torch.einsum("bhqd,bhkd->bhqk", q, k_cache) * (Dh ** -0.5)
        p = _softmax(scores, axis=-1)
        o = torch.einsum("bhqk,bhkd->bhqd", p, v_cache)
        return (lambda x, *d: x.permute(*d))(o, 0, 2, 1, 3).reshape(B, Sq, H * Dh) @ wo

    a = _A_ref(A_x, A_k_cache, A_v_cache, A_wq, A_wo)
    b = _B_ref(B_x, B_k_cache, B_v_cache, B_wq, B_wo)
    return torch.concatenate([a, b], axis=-1)
```

```cpp
#include <cuda_runtime.h>
#include <cuda_bf16.h>
#include <cuda.h>
#include <stdint.h>

namespace {

constexpr int NQ = 152;
constexpr uint32_t CH = 19456;
constexpr uint32_t OFF_RING = 6 * CH;
constexpr uint32_t TILE = 32768;
constexpr uint32_t OFF_STG = OFF_RING + 3 * TILE;
constexpr uint32_t OFF_MISC = OFF_STG + 16384;
constexpr uint32_t OFF_FULL = OFF_MISC;
constexpr uint32_t OFF_EMPTY = OFF_MISC + 32;
constexpr uint32_t OFF_FLAG = OFF_MISC + 64;
constexpr uint32_t OFF_EMIT = OFF_MISC + 72;
constexpr uint32_t OFF_RL = OFF_MISC + 128;
constexpr uint32_t SMEM_BYTES = OFF_MISC + 1024;
constexpr uint32_t S16 = 1024 >> 4;

constexpr int BAR_Z = 0, BAR_A = 1, BAR_B = 2, BAR_D = 3, BAR_E = 4, BAR_F = 5, BAR_G = 6  , BAR_C = 8  , BAR_H = 12  ,
              BAR_K = 14  ;

struct Params {
    CUtensorMap maps[16];
    __nv_bfloat16* out;
};

__device__ unsigned int g_zero_cnt[32];
#define PROF(role, idx) do {} while (0)
#define PROF2(role, idx) do {} while (0)

__device__ __forceinline__ void wg_fence() { asm volatile("wgmma.fence.sync.aligned;" ::: "memory"); }
__device__ __forceinline__ void wg_commit() { asm volatile("wgmma.commit_group.sync.aligned;" ::: "memory"); }
__device__ __forceinline__ void wg_wait0() { asm volatile("wgmma.wait_group.sync.aligned 0;" ::: "memory"); }
__device__ __forceinline__ void wg_wait1() { asm volatile("wgmma.wait_group.sync.aligned 1;" ::: "memory"); }
__device__ __forceinline__ void fence_async_smem() { asm volatile("fence.proxy.async.shared::cta;" ::: "memory"); }

template <int ID, int N> __device__ __forceinline__ void bar_sync() { asm volatile("bar.sync %0, %1;" ::"n"(ID), "n"(N) : "memory"); }
template <int ID, int N> __device__ __forceinline__ void bar_arrive() { asm volatile("bar.arrive %0, %1;" ::"n"(ID), "n"(N) : "memory"); }
template <int ID, int N> __device__ __forceinline__ void bar_sync_if(bool c) {
    asm volatile("{\n.reg .pred p;\nsetp.ne.b32 p, %0, 0;\n@p bar.sync %1, %2;\n}" ::"r"((int)c), "n"(ID), "n"(N) : "memory");
}
template <int ID, int N> __device__ __forceinline__ void bar_arrive_if(bool c) {
    asm volatile("{\n.reg .pred p;\nsetp.ne.b32 p, %0, 0;\n@p bar.arrive %1, %2;\n}" ::"r"((int)c), "n"(ID), "n"(N) : "memory");
}
__device__ __forceinline__ void cluster_sync_relaxed() {
    __syncwarp();
    asm volatile("barrier.cluster.arrive.relaxed.aligned;\nbarrier.cluster.wait.acquire.aligned;" ::: "memory");
}
__device__ __forceinline__ bool elect_one() {
    uint32_t p;
    asm volatile("{\n.reg .pred p;\nelect.sync _|p, 0xffffffff;\nselp.u32 %0, 1, 0, p;\n}" : "=r"(p));
    return p != 0;
}
__device__ __forceinline__ void mbar_wait(uint32_t bar, uint32_t parity) {
    asm volatile(
        "{\n.reg .pred p;\n.reg .u32 c;\nmov.u32 c, 0;\n"
        "W_LOOP:\n"
        "mbarrier.try_wait.parity.shared::cta.b64 p, [%0], %1;\n"
        "@p bra W_DONE;\n"
        "add.u32 c, c, 1;\n"
        "setp.lt.u32 p, c, 0x400000;\n"
        "@p bra W_LOOP;\n"
        "trap;\n"
        "W_DONE:\n}" ::"r"(bar), "r"(parity) : "memory");
}
__device__ __forceinline__ uint32_t mbar_test(uint32_t bar, uint32_t parity) {
    uint32_t ok;
    asm volatile("{\n.reg .pred p;\nmbarrier.test_wait.parity.shared::cta.b64 p, [%1], %2;\nselp.u32 %0, 1, 0, p;\n}" : "=r"(ok) : "r"(bar), "r"(parity) : "memory");
    return ok;
}
__device__ __forceinline__ void release_slot(uint32_t mapped_bar, int lane, uint32_t cnt) {
    asm volatile("{\n.reg .pred p;\nsetp.lt.s32 p, %1, 2;\n@p mbarrier.arrive.shared::cluster.b64 _, [%0], %2;\n}" ::"r"(mapped_bar),
                 "r"(lane), "r"(cnt) : "memory");
}
__device__ __forceinline__ int tid_now() { int t; asm volatile("mov.u32 %0, %%tid.x;" : "=r"(t)); return t & 127; }
__device__ __forceinline__ float ex2(float x) { float y; asm("ex2.approx.ftz.f32 %0, %1;" : "=f"(y) : "f"(x)); return y; }
__device__ __forceinline__ uint32_t pack2(float lo, float hi) { uint32_t r; asm("cvt.rn.bf16x2.f32 %0, %1, %2;" : "=r"(r) : "f"(hi), "f"(lo)); return r; }
__device__ __forceinline__ void stsm4t(uint32_t a, uint32_t r0, uint32_t r1, uint32_t r2, uint32_t r3) {
    asm volatile("stmatrix.sync.aligned.m8n8.x4.trans.shared.b16 [%0], {%1,%2,%3,%4};" ::"r"(a), "r"(r0), "r"(r1), "r"(r2), "r"(r3) : "memory");
}
__device__ __forceinline__ void stsm2t(uint32_t a, uint32_t r0, uint32_t r1) {
    asm volatile("stmatrix.sync.aligned.m8n8.x2.trans.shared.b16 [%0], {%1,%2};" ::"r"(a), "r"(r0), "r"(r1) : "memory");
}

#define R8(o) "%" #o "0,%" #o "1,%" #o "2,%" #o "3,%" #o "4,%" #o "5,%" #o "6,%" #o "7,%" #o "8,%" #o "9"
#define F4(d, i) "+f"(d[i]), "+f"(d[i + 1]), "+f"(d[i + 2]), "+f"(d[i + 3])
template <int TA>
__device__ __forceinline__ void mma152(float (&d)[76], uint32_t a16, uint32_t b16, int acc) {
    asm volatile(
        "{\n.reg .pred p;\n.reg .b64 da, db;\n"
        "setp.ne.b32 p, %78, 0;\n"
        "mov.b64 da, {%76, 0x40000040};\nmov.b64 db, {%77, 0x40000040};\n"
        "wgmma.mma_async.sync.aligned.m64n152k16.f32.bf16.bf16 "
        "{%0,%1,%2,%3,%4,%5,%6,%7,%8,%9," R8(1) "," R8(2) "," R8(3) "," R8(4) "," R8(5) "," R8(6) ",%70,%71,%72,%73,%74,%75}, "
        "da, db, p, 1, 1, %79, 0;\n}"
        : F4(d, 0), F4(d, 4), F4(d, 8), F4(d, 12), F4(d, 16), F4(d, 20), F4(d, 24), F4(d, 28), F4(d, 32), F4(d, 36), F4(d, 40), F4(d, 44),
          F4(d, 48), F4(d, 52), F4(d, 56), F4(d, 60), F4(d, 64), F4(d, 68), F4(d, 72)
        : "r"(a16), "r"(b16), "r"(acc), "n"(TA));
}
__device__ __forceinline__ void reg_fence(float (&d)[76]) {
#pragma unroll
    for (int i = 0; i < 76; i++) asm volatile("" : "+f"(d[i])::"memory");
}

struct Ring {
    uint32_t t6;
    __device__ __forceinline__ void adv(uint32_t n) { t6 += n; t6 = t6 >= 6 ? t6 - 6 : t6; }
    __device__ __forceinline__ uint32_t slot() const { return t6 >= 3 ? t6 - 3 : t6; }
    __device__ __forceinline__ uint32_t phase() const { return t6 >= 3 ? 1u : 0u; }
};

template <bool SCALE>
__device__ __forceinline__ void store_tile_t(const float (&d)[76], uint32_t addr, float c) {
#pragma unroll
    for (int j = 0; j < 18; j += 2) {
        const float* v = &d[4 * j];
        if (SCALE) stsm4t(addr + j * 1024, pack2(v[0] * c, v[1] * c), pack2(v[2] * c, v[3] * c), pack2(v[4] * c, v[5] * c), pack2(v[6] * c, v[7] * c));
        else stsm4t(addr + j * 1024, pack2(v[0], v[1]), pack2(v[2], v[3]), pack2(v[4], v[5]), pack2(v[6], v[7]));
    }
    if (SCALE) stsm2t(addr + 18 * 1024, pack2(d[72] * c, d[73] * c), pack2(d[74] * c, d[75] * c));
    else stsm2t(addr + 18 * 1024, pack2(d[72], d[73]), pack2(d[74], d[75]));
}

template <bool MAX>
__device__ __forceinline__ void column_reduce1(const float (&l)[38], uint32_t sbase) {
    const int tid = tid_now();
    const int lane = tid & 31, w = tid >> 5;
    auto op = [](float a, float b) { return MAX ? fmaxf(a, b) : a + b; };
    float a[20], b[10], c[5];
    const bool b4 = lane & 16, b3 = lane & 8, b2 = lane & 4;
#pragma unroll
    for (int i = 0; i < 20; i++) {
        float lo = l[i], hi = (i + 20 < 38) ? l[i + 20] : 0.f;
        a[i] = op(b4 ? hi : lo, __shfl_xor_sync(0xffffffffu, b4 ? lo : hi, 16));
    }
#pragma unroll
    for (int i = 0; i < 10; i++) b[i] = op(b3 ? a[i + 10] : a[i], __shfl_xor_sync(0xffffffffu, b3 ? a[i] : a[i + 10], 8));
#pragma unroll
    for (int i = 0; i < 5; i++) c[i] = op(b2 ? b[i + 5] : b[i], __shfl_xor_sync(0xffffffffu, b2 ? b[i] : b[i + 5], 4));
    const int c0 = (b4 ? 20 : 0) + (b3 ? 10 : 0) + (b2 ? 5 : 0);
#pragma unroll
    for (int i = 0; i < 5; i++) {
        const int ci = c0 + i;
        const int col = 8 * (ci >> 1) + 2 * (lane & 3) + (ci & 1);
        asm volatile("st.shared.f32 [%0], %1;" ::"r"(sbase + OFF_STG + (w * 160 + col) * 4), "f"(c[i]) : "memory");
    }
}
template <bool MAX>
__device__ __forceinline__ float2 column_reduce2(uint32_t sbase) {
    const int tid = tid_now();
    auto op = [](float a, float b) { return MAX ? fmaxf(a, b) : a + b; };
    float2 v[4];
#pragma unroll
    for (int k = 0; k < 4; k++)
        asm volatile("ld.shared.v2.f32 {%0,%1}, [%2];" : "=f"(v[k].x), "=f"(v[k].y) : "r"(sbase + OFF_STG + k * 640 + tid * 8) : "memory");
    return make_float2(op(op(v[0].x, v[1].x), op(v[2].x, v[3].x)), op(op(v[0].y, v[1].y), op(v[2].y, v[3].y)));
}
template <int N>
__device__ __forceinline__ void load_rl(float (&l)[N], uint32_t sbase) {
    const uint32_t a = sbase + OFF_RL + (tid_now() & 3) * 8;
#pragma unroll
    for (int c = 0; c < 19; c++) asm volatile("ld.shared.v2.f32 {%0,%1}, [%2];" : "=f"(l[2 * c]), "=f"(l[2 * c + 1]) : "r"(a + c * 32) : "memory");
}
template <int N>
__device__ __forceinline__ void store_out_tile(const float (&s)[76], const float (&l)[N], uint32_t a0, uint32_t a1) {
#pragma unroll
    for (int j = 0; j < 18; j += 2) {
        const float* v = &s[4 * j];
        const float* r = &l[2 * j];
        stsm4t(j < 16 ? a0 + j * 1024 : a1, pack2(v[0] * r[0], v[1] * r[1]), pack2(v[2] * r[0], v[3] * r[1]), pack2(v[4] * r[2], v[5] * r[3]),
               pack2(v[6] * r[2], v[7] * r[3]));
    }
    stsm2t(a1 + 2048, pack2(s[72] * l[36], s[73] * l[37]), pack2(s[74] * l[36], s[75] * l[37]));
}

template <bool SAFE>
__device__ __forceinline__ uint32_t softmax_block(const float (&s)[76], float (&l)[38], uint32_t paddr, uint32_t maddr, uint32_t nbar, uint32_t nphase) {
    uint32_t ok = 0;
#pragma unroll
    for (int j = 0; j < 19; j += 2) {
        uint32_t r[4];
#pragma unroll
        for (int jj = 0; jj < 2; jj++) {
            if (j + jj < 19) {
                const float* v = &s[4 * (j + jj)];
                float p0, p1, p2, p3;
                if (SAFE) {
                    float m0, m1;
                    asm volatile("ld.shared.v2.f32 {%0,%1}, [%2];" : "=f"(m0), "=f"(m1) : "r"(maddr + (j + jj) * 32) : "memory");
                    p0 = ex2(v[0] - m0); p1 = ex2(v[1] - m1); p2 = ex2(v[2] - m0); p3 = ex2(v[3] - m1);
                } else {
                    p0 = ex2(v[0]); p1 = ex2(v[1]); p2 = ex2(v[2]); p3 = ex2(v[3]);
                }
                l[2 * (j + jj)] += p0; l[2 * (j + jj) + 1] += p1;
                l[2 * (j + jj)] += p2; l[2 * (j + jj) + 1] += p3;
                r[2 * jj] = pack2(p0, p1); r[2 * jj + 1] = pack2(p2, p3);
            }
        }
        if (j + 1 < 19) stsm4t(paddr + j * 1024, r[0], r[1], r[2], r[3]);
        else stsm2t(paddr + j * 1024, r[0], r[1]);
        if (!SAFE && j == 14) ok = mbar_test(nbar, nphase);
    }
    return ok;
}

__device__ __forceinline__ uint32_t stsm_lane_off(int tid) {
    const int lane = tid & 31, w = (tid >> 5) & 3, mi = lane >> 3, r = lane & 7;
    return ((mi >> 1) * 8 + r) * 128 + (((2 * w + (mi & 1)) ^ r) << 4);
}

template <int TA, bool MAYBE_FIRST>
__device__ __forceinline__ void issue_s_op(float (&s)[76], uint32_t a16, bool first) {
#define S_QUARTER(c)                                                                                                   \
    if (MAYBE_FIRST && c > 0) bar_sync_if<BAR_C + c, 256>(first);                                                      \
    if (c == 0) wg_fence();                                                                                            \
    _Pragma("unroll") for (int k = 0; k < 4; k++) mma152<TA>(s, a16 + c * 512 + k * (TA ? 128 : 2), S16 + c * (CH >> 4) + k * 2, c + k > 0);
    S_QUARTER(0) S_QUARTER(1) S_QUARTER(2) S_QUARTER(3)
#undef S_QUARTER
    wg_commit();
}
__device__ __forceinline__ uint32_t slot16(uint32_t sl) { return S16 + ((OFF_RING + sl * TILE) >> 4); }

__device__ __forceinline__ uint32_t s_round(const uint32_t sbase, const int tid, Ring& ring, const int nu, const bool safe, const bool emit_in,
                                            const uint32_t rel0, const uint32_t rank) {
    const int lane = tid & 31;
    const uint32_t lane_off = stsm_lane_off(tid);
    float s[76], l[38];
    uint32_t bad = 0;
    ring.adv(1);
#pragma unroll 1
    for (int u = 0; u < nu; u++) {
        const bool paired = u + 1 < nu;
#pragma unroll 1
        for (int pass = safe ? 0 : 1; pass < 2; pass++) {
            const float init = pass == 0 ? -INFINITY : 0.f;
#pragma unroll
            for (int i = 0; i < 38; i++) l[i] = init;
            uint32_t sl = ring.slot();
            {
                const bool first = pass == 0 || !safe;
                bar_sync_if<BAR_C, 256>(first && u == 0);
                mbar_wait(sbase + OFF_FULL + sl * 8, ring.phase());
                bar_sync_if<BAR_C, 256>(first && u > 0);
                issue_s_op<0, true>(s, slot16(sl), first);
                PROF(0, u * 128 + 2);
            }
#pragma unroll 1
            for (int j = 0; j < 16; j++) {
                ring.adv((j == 0 || pass == 0) ? 1 : (j == 15 ? 3 : 2));
                const uint32_t rel = rel0 + sl * 8;
                sl = ring.slot();
                const uint32_t nbar = sbase + OFF_FULL + sl * 8, nphase = ring.phase(), na16 = slot16(sl);
                const uint32_t pa = sbase + (4 + (j & 1)) * CH + lane_off;
                bar_sync_if<BAR_K, 160>(j == 1 && u > 0);
                wg_wait0();
                reg_fence(s);
                PROF2(0, u * 128 + j * 4 + 3);
                release_slot(rel, lane, 2);
                uint32_t ready = 0;
                if (!safe) ready = softmax_block<false>(s, l, pa, 0, nbar, nphase);
                else if (pass == 1) softmax_block<true>(s, l, pa, sbase + OFF_RL + (tid_now() & 3) * 8, 0, 0);
                else {
#pragma unroll
                    for (int c = 0; c < 19; c++) {
                        l[2 * c] = fmaxf(l[2 * c], fmaxf(s[4 * c], s[4 * c + 2]));
                        l[2 * c + 1] = fmaxf(l[2 * c + 1], fmaxf(s[4 * c + 1], s[4 * c + 3]));
                    }
                }
                if (j < 15) {
                    PROF2(0, u * 128 + j * 4 + 4);
                    if (!ready) mbar_wait(nbar, nphase);
                    issue_s_op<0, false>(s, na16, false);
                }
                fence_async_smem();
                bar_sync_if<BAR_A, 384>(pass == 1);
                PROF(0, j < 15 ? u * 128 + j * 4 + 6 : 999);
            }
            wg_wait0();
            if (pass == 0) {
                column_reduce1<true>(l, sbase);
                bar_sync<BAR_E, 128>();
                const float2 m = column_reduce2<true>(sbase);
                const int t = tid_now();
                if (t < 76) asm volatile("st.shared.v2.f32 [%0], {%1,%2};" ::"r"(sbase + OFF_RL + t * 8), "f"(m.x), "f"(m.y) : "memory");
                bar_sync<BAR_E, 128>();
            }
        }
#pragma unroll
        for (int i = 0; i < 38; i++) asm volatile("" : "+f"(l[i])::"memory");
        column_reduce1<false>(l, sbase);
        bool emit = false;
#pragma unroll 1
        for (int i = 0; i < 7; i += paired ? 1 : 2) {
            const uint32_t sl = ring.slot();
            PROF2(0, u * 128 + 64 + i * 4);
            mbar_wait(sbase + OFF_FULL + sl * 8, ring.phase());
            bar_sync_if<BAR_D, 256>(i > 0 && paired);
            bar_sync_if<BAR_C, 256>(i == 0 || !paired);
            PROF2(0, u * 128 + 64 + i * 4 + 1);
            issue_s_op<1, true>(s, slot16(sl), i == 0);
            bar_sync_if<BAR_A, 384>(paired);
            bar_arrive_if<BAR_G, 256>(!paired && i < 6);
            PROF(0, u * 128 + 64 + i * 4 + 2);
            ring.adv(paired || i < 6 ? 2 : 1);
            if (i == 0) {
                bar_sync<BAR_E, 128>();
                const float2 t = column_reduce2<false>(sbase);
                const int tn = tid_now();
                const bool oob = tn < 76 && !(t.x >= 0x1p-30f && t.x <= 0x1p40f && t.y >= 0x1p-30f && t.y <= 0x1p40f);
                float rx, ry;
                asm("rcp.approx.ftz.f32 %0, %1;" : "=f"(rx) : "f"(t.x));
                asm("rcp.approx.ftz.f32 %0, %1;" : "=f"(ry) : "f"(t.y));
                if (tn < 76) asm volatile("st.shared.v2.f32 [%0], {%1,%2};" ::"r"(sbase + OFF_RL + tn * 8), "f"(rx), "f"(ry) : "memory");
                uint32_t any;
                asm volatile("{\n.reg .pred p, q;\nsetp.ne.b32 p, %1, 0;\nbar.red.or.pred q, %2, 128, p;\nselp.u32 %0, 1, 0, q;\n}"
                             : "=r"(any) : "r"((int)oob), "n"(BAR_E) : "memory");
                any = __shfl_sync(0xffffffffu, any, 0);
                emit = safe ? emit_in : any == 0;
                bad |= any << u;
                load_rl(l, sbase);
                asm volatile("st.shared.u32 [%0], %1;" ::"r"(sbase + OFF_EMIT), "r"((uint32_t)emit) : "memory");
                if (!safe && !paired) {
                    asm volatile("st.shared::cluster.u32 [%0], %1;" ::"r"(rel0 - OFF_EMPTY + OFF_FLAG + rank * 4), "r"(bad) : "memory");
                }
            }
            bar_sync_if<BAR_K, 160>(i > 0);
            wg_wait0();
            reg_fence(s);
            PROF2(0, u * 128 + 64 + i * 4 + 3);
            release_slot(rel0 + sl * 8, lane, 2);
            bar_arrive_if<BAR_G, 256>(paired && i == 6);
            bar_arrive_if<BAR_G + 1, 256>(paired && i == 6);
            if (emit) store_out_tile(s, l, sbase + (paired ? OFF_STG : 4 * CH) + lane_off, sbase + (paired ? 5 - (i & 1) : 4) * CH + 16384 + lane_off);
            fence_async_smem();
            bar_arrive<BAR_H, 160>();
        }
    }
    asm volatile("fence.acq_rel.cluster;" ::: "memory");
    return bad;
}

struct Producer {
    Ring ring;
    int pu, pp;
    const CUtensorMap *map, *xmap;
    int c0, c1, c2;
    uint32_t xdst;
    uint64_t pol;
};
constexpr uint64_t POL_FIRST = 0x12F0000000000000ull, POL_NORMAL = 0x16F0000000000000ull;

__device__ __forceinline__ void decode(const Params& p, Producer& pr, const uint32_t sbase, const int br, const int bh0, const uint32_t rank) {
    const int pp = pr.pp;
    const int bh = bh0 + 4 * pr.pu;
    int mi, c0 = 0, c1, c2;
    uint32_t xdst = 0;
    if (pp < -16) { const int xi = pp + 23; mi = 3; c1 = xi * 64; c2 = (bh & 15) * 4 + 2 * rank; xdst = sbase + ((0x4503210 >> (4 * xi)) & 7) * CH; }
    else if (pp < 32) {
        const bool isk = pp <= 0 || ((pp & 1) && pp != 31);
        const int j = pp < 0 ? pp + 16 : (isk ? (pp + 1) >> 1 : (pp == 31 ? 15 : (pp >> 1) - 1));
        mi = isk ? 1 : 2; c1 = bh * 1024 + j * 64; c2 = 2 * rank;
    } else if (pp & 1) { const int xi = (pp - 32) >> 1; mi = 3; c1 = xi * 64; c2 = ((bh + 4) & 15) * 4 + 2 * rank; xdst = sbase + (4 + (xi & 1)) * CH; }
    else { mi = 4; c0 = (pp - 32) * 32; c1 = (bh & 15) * 256 + 128 * rank; c2 = 0; }
    pr.map = &p.maps[br * 7 + mi];
    pr.xmap = &p.maps[br * 7 + (pp > 33 ? 5 : 0)];
    pr.c0 = c0; pr.c1 = c1; pr.c2 = c2; pr.xdst = xdst;
    pr.pol = mi <= 2 ? POL_FIRST : POL_NORMAL;
}

__device__ __forceinline__ void tma_load_2d(uint32_t dst, const CUtensorMap* m, uint32_t bar, int c0, int c1) {
    asm volatile("cp.async.bulk.tensor.2d.shared::cluster.global.mbarrier::complete_tx::bytes [%0], [%1, {%3, %4}], [%2];" ::"r"(dst), "l"(m), "r"(bar),
                 "r"(c0), "r"(c1) : "memory");
}
__device__ __forceinline__ void tma_add_2d(const CUtensorMap* m, int c0, int c1, uint32_t src) {
    asm volatile("cp.reduce.async.bulk.tensor.2d.global.shared::cta.add.tile.bulk_group [%0, {%1, %2}], [%3];" ::"l"(m), "r"(c0), "r"(c1), "r"(src) : "memory");
    asm volatile("cp.async.bulk.commit_group;" ::: "memory");
}

__device__ __forceinline__ void refill(const Params& p, Producer& pr, const uint32_t sbase, const int nu, const bool safe, const int br,
                                       const int bh0, const int row0, const uint32_t rank) {
    if (pr.pu >= nu) return;
    const uint32_t sl = pr.ring.slot();
    const uint32_t full = sbase + OFF_FULL + sl * 8;
    const uint32_t dst = sbase + OFF_RING + sl * TILE + rank * 16384;
    const uint32_t bytes = pr.xdst ? TILE + CH : TILE;
    mbar_wait(full + (OFF_EMPTY - OFF_FULL), pr.ring.phase() ^ 1);
    if (elect_one()) {
        asm volatile("mbarrier.arrive.expect_tx.shared::cta.b64 _, [%0], %1;" ::"r"(full), "r"(bytes) : "memory");
        asm volatile(
            "cp.async.bulk.tensor.3d.shared::cluster.global.mbarrier::complete_tx::bytes.multicast::cluster.L2::cache_hint [%0], [%1, {%3, %4, %5}], [%2], %6, %7;" ::"r"(dst),
            "l"(pr.map), "r"(full), "r"(pr.c0), "r"(pr.c1), "r"(pr.c2), "h"((uint16_t)3), "l"(pr.pol) : "memory");
        if (pr.xdst) tma_load_2d(pr.xdst, pr.xmap, full, pr.c1, row0);
    }
    pr.ring.adv(1);
    const int pp = pr.pp;
    int np = pp + 1;
    if (np == -16 && !safe) np = 0;
    if (np > 32 && pr.pu + 1 == nu) np = pp + 2;
    if (np >= 46) { np = 0; pr.pu++; }
    pr.pp = np;
    decode(p, pr, sbase, br, bh0, rank);
}

__device__ __forceinline__ void emit_tile(const Params& p, const uint32_t sbase, const int i, const uint32_t a0, const uint32_t a1, const int br,
                                          const int row0) {
    uint32_t emit;
    asm volatile("ld.shared.u32 %0, [%1];" : "=r"(emit) : "r"(sbase + OFF_EMIT) : "memory");
    if (elect_one() && emit) {
        tma_add_2d(&p.maps[15], br * 448 + i * 64, row0 + 128, a1);
        tma_add_2d(&p.maps[14], br * 448 + i * 64, row0, a0);
    }
    __syncwarp();
}

template <int OID>
__device__ __forceinline__ void o_round(const Params& p, const uint32_t sbase, const int tid, const int warp, Ring& ring, Producer& pr, const int nu,
                                        const bool safe, const uint32_t rel0, const int br, const int bh0, const int row0, const uint32_t rank) {
    const int lane = tid & 31;
    const bool lead = (warp & 3) == 0;
    float o0[76], o1[76];
    uint32_t zero_target = 0;
    if (OID == 0 && lead) {
        pr.pu = 0; pr.pp = -23;
        decode(p, pr, sbase, br, bh0, rank);
#pragma unroll 1
        for (int i = 0; i < 3; i++) refill(p, pr, sbase, nu, safe, br, bh0, row0, rank);
    }
#pragma unroll 1
    for (int ph = 0; ph < 2 * nu; ph++) {
        const bool isq = (ph & 1) == 0, pro = ph == 0;
        const int nops = isq ? 7 : 16;
        if (OID == 1) {
            bar_arrive_if<BAR_A, 384>(!pro);
            if (ph == 2 && lead) {
                        asm volatile(
                            "{\n.reg .pred p;\n.reg .u32 c, v;\nmov.u32 c, 0;\n"
                            "Z_LOOP:\n"
                            "ld.acquire.gpu.global.u32 v, [%0];\n"
                            "sub.u32 v, v, %1;\n"
                            "setp.ge.s32 p, v, 0;\n"
                            "vote.sync.all.pred p, p, 0xffffffff;\n"
                            "@p bra.uni Z_DONE;\n"
                            "add.u32 c, c, 1;\n"
                            "setp.lt.u32 p, c, 0x1000000;\n"
                            "@p bra.uni Z_LOOP;\n"
                            "trap;\n"
                            "Z_DONE:\n"
                            "fence.proxy.async;\n}" ::"l"(&g_zero_cnt[(br * 8 + (bh0 >> 4)) * 2 + rank]), "r"(zero_target) : "memory");
            }
        } else if (!pro && lead) {
            const int n = isq ? 1 : (safe ? 18 : 2);
#pragma unroll 1
            for (int i = 0; i < n; i++) refill(p, pr, sbase, nu, safe, br, bh0, row0, rank);
        }
#pragma unroll 1
        for (int i = 0; i < nops; i++) {
            const uint32_t sl = ring.slot();
            const uint32_t a16 = slot16(sl) + OID * 1024;
            const uint32_t bi = pro ? (0x4503210 >> (4 * i)) & 7 : 4 + (i & 1);
            const uint32_t b16 = S16 + bi * (CH >> 4);
            const bool last = i + 1 == nops;
            PROF2(1 + OID, ph * 64 + i * 4);
            if (i == 15) mbar_wait(sbase + OFF_FULL + sl * 8, ring.phase());
            if (OID == 0) {
                bar_sync_if<BAR_A, 384>(!pro);
                bar_sync_if<BAR_F, 256>(pro && i > 0);
            } else {
                bar_sync<BAR_B, 256>();
            }
            PROF2(1 + OID, ph * 64 + i * 4 + 1);
            if (i != 15) mbar_wait(sbase + OFF_FULL + sl * 8, ring.phase());
            wg_fence();
#pragma unroll
            for (int k = 0; k < 4; k++) mma152<1>(o0, a16 + k * 128, b16 + k * 2, k > 0 || i > 0);
            wg_commit();
#pragma unroll
            for (int k = 0; k < 4; k++) mma152<1>(o1, a16 + 512 + k * 128, b16 + k * 2, k > 0 || i > 0);
            wg_commit();
            uint32_t n = 2;
            if (pro || i == 14) n = 1;
            if (last) n = isq ? (safe ? 1 : 3) : 2;
            ring.adv(n);
            if (OID == 0) {
                bar_arrive<BAR_B, 256>();
                if (lead && !(pro && i == 0)) refill(p, pr, sbase, nu, safe, br, bh0, row0, rank);
            } else {
                bar_arrive_if<BAR_F, 256>(pro && !last);
                bar_arrive_if<BAR_D, 256>(isq && !pro && !last);
                bar_arrive_if<BAR_A, 384>(i == 14);
                if (lead && isq && !pro) {
                    const uint32_t tail = sbase + (5 - (i & 1)) * CH + 16384;
                    bar_sync<BAR_H, 160>();
                    emit_tile(p, sbase, i, sbase + OFF_STG, tail, br, row0);
                    if (!last) {
                        asm volatile("cp.async.bulk.wait_group.read 1;" ::: "memory");
                        if (elect_one()) tma_load_2d(tail, &p.maps[br * 7 + 6], sbase + OFF_FULL + ring.slot() * 8, (i + 1) * 64, row0 + 128);
                        __syncwarp();
                    }
                }
            }
            PROF2(1 + OID, ph * 64 + i * 4 + 2);
            if (last) {
                const uint32_t qa = sbase + OID * 2 * CH + stsm_lane_off(tid_now());
                const float c = 0.0625f * 1.4426950408889634f;
                bar_sync_if<BAR_G + OID, 256>(isq && !pro);
                wg_wait1();
                reg_fence(o0);
                if (isq) store_tile_t<true>(o0, qa, c); else store_tile_t<false>(o0, qa, c);
                fence_async_smem();
                bar_arrive<BAR_C + 2 * OID, 256>();
                wg_wait0();
                reg_fence(o1);
                release_slot(rel0 + sl * 8, lane, 1);
                if (isq) store_tile_t<true>(o1, qa + CH, c); else store_tile_t<false>(o1, qa + CH, c);
                fence_async_smem();
                bar_arrive<BAR_C + 2 * OID + 1, 256>();
                PROF2(1 + OID, ph * 64 + i * 4 + 3);
            } else {
                wg_wait0();
                reg_fence(o0);
                reg_fence(o1);
                PROF2(1 + OID, ph * 64 + i * 4 + 3);
                release_slot(rel0 + sl * 8, lane, 1);
                if (OID == 0) {
                    if (lead && !pro && i != 14) refill(p, pr, sbase, nu, safe, br, bh0, row0, rank);
                } else {
                    bar_arrive_if<BAR_A, 384>(!pro && i != 14);
                }
            }
            if (OID == 1) {
                if (lead && isq && !pro) {
                    asm volatile("cp.async.bulk.wait_group.read 0;" ::: "memory");
                    __syncwarp();
                    bar_arrive<BAR_K, 160>();
                }
                if (ph == 1 && !safe) {
                    unsigned int* cnt = &g_zero_cnt[(br * 8 + (bh0 >> 4)) * 2 + rank];
                    if (i < 10) {
                        const int t = tid_now();
                        uint4* z = reinterpret_cast<uint4*>(p.out + (uint32_t)((row0 + (bh0 & 3) * 38 + i * 4) * 896 + br * 448)) + (t >> 6) * 112 + (t & 63);
                        if ((t & 63) < 56) z[0] = make_uint4(0, 0, 0, 0);
                        if ((t & 63) < 56 && i < 9) z[224] = make_uint4(0, 0, 0, 0);
                    } else if (i == 10) {
                        asm volatile("fence.proxy.async;" ::: "memory");
                        __threadfence();
                        bar_sync<BAR_Z, 128>();
                        if (lead) {
                            if (elect_one()) zero_target = (atomicAdd(cnt, 1u) & ~3u) + 4u;
                            zero_target = __reduce_or_sync(0xffffffffu, zero_target);
                        }
                    }
                }
            }
        }
    }
    if (OID == 0) {
        if (lead) refill(p, pr, sbase, nu, safe, br, bh0, row0, rank);
#pragma unroll 1
        for (int i = 1; i < 7; i += 2) {
            const uint32_t sl = ring.slot();
            bar_sync<BAR_G, 256>();
            mbar_wait(sbase + OFF_FULL + sl * 8, ring.phase());
            issue_s_op<1, true>(o0, slot16(sl), false);
            bar_arrive<BAR_C, 256>();
            if (lead) refill(p, pr, sbase, nu, safe, br, bh0, row0, rank);
            ring.adv(2);
            bar_sync<BAR_K + 1, 160>();
            uint32_t emit;
            asm volatile("ld.shared.u32 %0, [%1];" : "=r"(emit) : "r"(sbase + OFF_EMIT) : "memory");
            load_rl(o1, sbase);
            emit = __shfl_sync(0xffffffffu, emit, 0);
            wg_wait0();
            reg_fence(o0);
            release_slot(rel0 + sl * 8, lane, 2);
            const uint32_t a = sbase + 5 * CH + stsm_lane_off(tid_now());
            if (emit) store_out_tile(o0, o1, a, a + 16384);
            fence_async_smem();
            bar_arrive<BAR_H + 1, 160>();
            if (lead) refill(p, pr, sbase, nu, safe, br, bh0, row0, rank);
        }
    } else if (lead) {
#pragma unroll 1
        for (int i = 0; i < 7; i++) {
            bar_sync_if<BAR_H, 160>(!(i & 1));
            bar_sync_if<BAR_H + 1, 160>(i & 1);
            const uint32_t a = sbase + (4 + (i & 1)) * CH;
            emit_tile(p, sbase, i, a, a + 16384, br, row0);
            asm volatile("cp.async.bulk.wait_group.read 2;" ::: "memory");
            __syncwarp();
            bar_arrive_if<BAR_K, 160>(i & 1);
            bar_arrive_if<BAR_K + 1, 160>(!(i & 1) && i < 6);
        }
        asm volatile("cp.async.bulk.wait_group.read 0;" ::: "memory");
    }
}

__device__ __forceinline__ uint32_t read_redo(uint32_t sbase) {
    uint32_t a, b;
    asm volatile("ld.shared.v2.u32 {%0,%1}, [%2];" : "=r"(a), "=r"(b) : "r"(sbase + OFF_FLAG) : "memory");
    return __shfl_sync(0xffffffffu, a | b, 0);
}

template <int OID>
__device__ __forceinline__ void o_role(const Params& p, const uint32_t sbase, const int tid, const int warp, const uint32_t rel0, const int br,
                                       const int bh_first, const int row0, const uint32_t rank) {
    Ring ring; ring.t6 = 0;
    Producer pr; pr.ring.t6 = 0;
    uint32_t redo = 0;
#pragma unroll 1
    for (int r = -1; r < 4; r++) {
        if (r < 0 || ((redo >> r) & 1)) {
            o_round<OID>(p, sbase, tid, warp, ring, pr, r < 0 ? 4 : 1, r >= 0, rel0, br, r < 0 ? bh_first : bh_first + 4 * r, row0, rank);
            cluster_sync_relaxed();
            if (r < 0) redo = read_redo(sbase);
        }
    }
}

__global__ void __cluster_dims__(2, 1, 1) __launch_bounds__(384, 1) fused_mha_kernel(const __grid_constant__ Params p) {
    extern __shared__ __align__(1024) uint8_t smem_raw[];
    const uint32_t sbase = (uint32_t)__cvta_generic_to_shared(smem_raw);
    const int warp = __shfl_sync(0xffffffffu, threadIdx.x >> 5, 0);
    const int tid = threadIdx.x & 127;
    const uint32_t rank = blockIdx.x & 1;
    const int cl = blockIdx.x >> 1;
    const int bb = cl >> 2;
    const int br = bb >> 3;
    const int bh_first = (bb & 7) * 16 + (cl & 3);
    const int row0 = (bb & 7) * 304 + rank * NQ;
    if (warp == 4) {
        if (elect_one()) {
            asm volatile("prefetch.tensormap [%0];" ::"l"(&p.maps[br * 7 + 3]) : "memory");
            asm volatile("prefetch.tensormap [%0];" ::"l"(&p.maps[br * 7]) : "memory");
        }
    }
    if (warp == 0) {
        if (elect_one()) {
            for (int i = 0; i < 3; i++) {
                asm volatile("mbarrier.init.shared::cta.b64 [%0], 1;" ::"r"(sbase + OFF_FULL + i * 8) : "memory");
                asm volatile("mbarrier.init.shared::cta.b64 [%0], 16;" ::"r"(sbase + OFF_EMPTY + i * 8) : "memory");
            }
            asm volatile("fence.mbarrier_init.release.cluster;" ::: "memory");
        }
    }
    asm volatile("{\n.reg .pred p;\nsetp.ne.u32 p, %0, 1024;\n@p trap;\n}" ::"r"(sbase & 0x3FFFF));
    uint32_t rel0;
    asm volatile("mapa.shared::cluster.u32 %0, %1, %2;" : "=r"(rel0) : "r"(sbase + OFF_EMPTY), "r"(threadIdx.x & 1));
    cluster_sync_relaxed();

    if (warp < 4) {
        asm volatile("setmaxnreg.dec.sync.aligned.u32 136;");
        Ring ring; ring.t6 = 0;
        uint32_t redo = 0, bad = 0;
#pragma unroll 1
        for (int r = -1; r < 4; r++) {
            if (r < 0 || ((redo >> r) & 1)) {
                const uint32_t b = s_round(sbase, tid, ring, r < 0 ? 4 : 1, r >= 0, r >= 0 && ((bad >> r) & 1), rel0, rank);
                cluster_sync_relaxed();
                if (r < 0) { bad = b; redo = read_redo(sbase); }
            }
        }
    } else {
        asm volatile("setmaxnreg.inc.sync.aligned.u32 184;");
        if (warp < 8) o_role<0>(p, sbase, tid, warp, rel0, br, bh_first, row0, rank);
        else o_role<1>(p, sbase, tid, warp, rel0, br, bh_first, row0, rank);
    }
}

typedef CUresult (*EncodeFn)(CUtensorMap*, CUtensorMapDataType, cuuint32_t, void*, const cuuint64_t*, const cuuint64_t*, const cuuint32_t*,
                             const cuuint32_t*, CUtensorMapInterleave, CUtensorMapSwizzle, CUtensorMapL2promotion, CUtensorMapFloatOOBfill);

void encode(EncodeFn fn, CUtensorMap* m, void* ptr, int rank, uint64_t d0, uint64_t d1, uint64_t d2, uint64_t s1, uint64_t s2, uint32_t b0,
            uint32_t b1, uint32_t b2) {
    cuuint64_t dims[3] = {d0, d1, d2};
    cuuint64_t strides[2] = {s1, s2};
    cuuint32_t box[3] = {b0, b1, b2};
    cuuint32_t es[3] = {1, 1, 1};
    fn(m, CU_TENSOR_MAP_DATA_TYPE_BFLOAT16, rank, ptr, dims, strides, box, es, CU_TENSOR_MAP_INTERLEAVE_NONE, CU_TENSOR_MAP_SWIZZLE_128B,
       CU_TENSOR_MAP_L2_PROMOTION_L2_256B, CU_TENSOR_MAP_FLOAT_OOB_FILL_NONE);
}

}

extern "C" void kernel_launch(void* const* d_in, const int* in_sizes, int n_in, void* d_out, int out_size) {
    (void)in_sizes; (void)n_in; (void)out_size;
    static EncodeFn fn = nullptr;
    if (!fn) {
        void* f = nullptr;
        cudaDriverEntryPointQueryResult q;
        cudaGetDriverEntryPoint("cuTensorMapEncodeTiled", &f, cudaEnableDefault, &q);
        fn = (EncodeFn)f;
        cudaFuncSetAttribute(fused_mha_kernel, cudaFuncAttributeMaxDynamicSharedMemorySize, SMEM_BYTES);
    }
    Params p;
    for (int br = 0; br < 2; br++) {
        void* const* in = d_in + br * 5;
        CUtensorMap* m = p.maps + br * 7;
        encode(fn, m + 0, in[0], 2, 448, 2432, 1, 896, 0, 64, NQ, 1);
        encode(fn, m + 1, in[1], 3, 64, 131072, 4, 512, 128, 64, 64, 2);
        encode(fn, m + 2, in[2], 3, 64, 131072, 4, 512, 128, 64, 64, 2);
        encode(fn, m + 3, in[3], 3, 64, 448, 64, 8192, 128, 64, 64, 2);
        encode(fn, m + 4, in[4], 3, 448, 4096, 1, 896, 896 * 4096, 64, 128, 1);
        encode(fn, m + 5, in[0], 2, 448, 2432, 1, 896, 0, 64, 128, 1);
        encode(fn, m + 6, in[0], 2, 448, 2432, 1, 896, 0, 64, 24, 1);
    }
    encode(fn, p.maps + 14, d_out, 2, 896, 2432, 1, 1792, 0, 64, 128, 1);
    encode(fn, p.maps + 15, d_out, 2, 896, 2432, 1, 1792, 0, 64, 24, 1);
    p.out = (__nv_bfloat16*)d_out;
    fused_mha_kernel<<<128, 384, SMEM_BYTES>>>(p);
}
```

```cpp
#include <cuda_runtime.h>
#include <cuda_bf16.h>
#include <cuda.h>
#include <stdint.h>

namespace {

constexpr int NQ = 152;
constexpr uint32_t CH = 19456;
constexpr uint32_t OFF_RING = 6 * CH;
constexpr uint32_t TILE = 32768;
constexpr uint32_t OFF_STG = OFF_RING + 3 * TILE;
constexpr uint32_t OFF_MISC = OFF_STG + 16384;
constexpr uint32_t OFF_FULL = OFF_MISC;
constexpr uint32_t OFF_EMPTY = OFF_MISC + 32;
constexpr uint32_t OFF_FLAG = OFF_MISC + 64;
constexpr uint32_t OFF_EMIT = OFF_MISC + 72;
constexpr uint32_t OFF_ZT = OFF_MISC + 76;
constexpr uint32_t OFF_RL = OFF_MISC + 128;
constexpr uint32_t SMEM_BYTES = OFF_MISC + 1024;
constexpr uint32_t S16 = 1024 >> 4;

constexpr int BAR_T = 0, BAR_A = 1, BAR_B = 2, BAR_D = 3, BAR_E = 4, BAR_F = 5, BAR_G = 6  , BAR_C = 8  , BAR_H = 12  ,
              BAR_K = 14  ;

#define CHAIN_D 2
#define PROMO CU_TENSOR_MAP_L2_PROMOTION_NONE
#define LSPLIT 0
struct Params {
    CUtensorMap maps[12];
    __nv_bfloat16* out;
};

__device__ unsigned int g_zero_cnt;
__device__ unsigned int g_epoch[128];
#define PROF(role, idx) do {} while (0)
#define GT(idx) do {} while (0)
#define TS(v) do {} while (0)
#define PROF2(role, idx) do {} while (0)

__device__ __forceinline__ void wg_fence() { asm volatile("wgmma.fence.sync.aligned;" ::: "memory"); }
__device__ __forceinline__ void wg_commit() { asm volatile("wgmma.commit_group.sync.aligned;" ::: "memory"); }
__device__ __forceinline__ void wg_wait0() { asm volatile("wgmma.wait_group.sync.aligned 0;" ::: "memory"); }
__device__ __forceinline__ void wg_wait1() { asm volatile("wgmma.wait_group.sync.aligned 1;" ::: "memory"); }
__device__ __forceinline__ void fence_async_smem() { asm volatile("fence.proxy.async.shared::cta;" ::: "memory"); }

template <int ID, int N> __device__ __forceinline__ void bar_sync() { asm volatile("bar.sync %0, %1;" ::"n"(ID), "n"(N) : "memory"); }
template <int ID, int N> __device__ __forceinline__ void bar_arrive() { asm volatile("bar.arrive %0, %1;" ::"n"(ID), "n"(N) : "memory"); }
template <int ID, int N> __device__ __forceinline__ void bar_sync_if(bool c) {
    asm volatile("{\n.reg .pred p;\nsetp.ne.b32 p, %0, 0;\n@p bar.sync %1, %2;\n}" ::"r"((int)c), "n"(ID), "n"(N) : "memory");
}
template <int ID, int N> __device__ __forceinline__ void bar_sync_if_after(bool c, uint32_t a, uint32_t b) {
    asm volatile("{\n.reg .pred p;\nsetp.ne.b32 p, %0, 0;\nsetp.ne.and.b32 p, %3, 0, p;\nsetp.ne.and.b32 p, %4, 0, p;\n@p bar.sync %1, %2;\n}" ::"r"((int)c),
                 "n"(ID), "n"(N), "r"(a), "r"(b) : "memory");
}
template <int ID, int N> __device__ __forceinline__ void bar_arrive_if(bool c) {
    asm volatile("{\n.reg .pred p;\nsetp.ne.b32 p, %0, 0;\n@p bar.arrive %1, %2;\n}" ::"r"((int)c), "n"(ID), "n"(N) : "memory");
}
__device__ __forceinline__ void cluster_sync_relaxed() {
    __syncwarp();
    asm volatile("barrier.cluster.arrive.relaxed.aligned;\nbarrier.cluster.wait.acquire.aligned;" ::: "memory");
}
__device__ __forceinline__ bool elect_one() {
    uint32_t p;
    asm volatile("{\n.reg .pred p;\nelect.sync _|p, 0xffffffff;\nselp.u32 %0, 1, 0, p;\n}" : "=r"(p));
    return p != 0;
}
__device__ __forceinline__ void mbar_wait(uint32_t bar, uint32_t parity) {
    asm volatile(
        "{\n.reg .pred p;\n.reg .u32 c;\nmov.u32 c, 0;\n"
        "W_LOOP:\n"
        "mbarrier.try_wait.parity.shared::cta.b64 p, [%0], %1;\n"
        "@p bra W_DONE;\n"
        "add.u32 c, c, 1;\n"
        "setp.lt.u32 p, c, 0x400000;\n"
        "@p bra W_LOOP;\n"
        "trap;\n"
        "W_DONE:\n}" ::"r"(bar), "r"(parity) : "memory");
}
__device__ __forceinline__ uint32_t mbar_test(uint32_t bar, uint32_t parity) {
    uint32_t ok;
    asm volatile("{\n.reg .pred p;\nmbarrier.test_wait.parity.shared::cta.b64 p, [%1], %2;\nselp.u32 %0, 1, 0, p;\n}" : "=r"(ok) : "r"(bar), "r"(parity) : "memory");
    return ok;
}
__device__ __forceinline__ void release_slot(uint32_t mapped_bar, int lane, uint32_t cnt) {
    asm volatile("{\n.reg .pred p;\nsetp.lt.s32 p, %1, 2;\n@p mbarrier.arrive.shared::cluster.b64 _, [%0], %2;\n}" ::"r"(mapped_bar),
                 "r"(lane), "r"(cnt) : "memory");
}
__device__ __forceinline__ int tid_now() { int t; asm volatile("mov.u32 %0, %%tid.x;" : "=r"(t)); return t & 127; }
__device__ __forceinline__ float ex2(float x) { float y; asm("ex2.approx.ftz.f32 %0, %1;" : "=f"(y) : "f"(x)); return y; }
__device__ __forceinline__ uint32_t pack2(float lo, float hi) { uint32_t r; asm("cvt.rn.bf16x2.f32 %0, %1, %2;" : "=r"(r) : "f"(hi), "f"(lo)); return r; }
__device__ __forceinline__ void stsm4t(uint32_t a, uint32_t r0, uint32_t r1, uint32_t r2, uint32_t r3) {
    asm volatile("stmatrix.sync.aligned.m8n8.x4.trans.shared.b16 [%0], {%1,%2,%3,%4};" ::"r"(a), "r"(r0), "r"(r1), "r"(r2), "r"(r3) : "memory");
}
__device__ __forceinline__ void stsm2t(uint32_t a, uint32_t r0, uint32_t r1) {
    asm volatile("stmatrix.sync.aligned.m8n8.x2.trans.shared.b16 [%0], {%1,%2};" ::"r"(a), "r"(r0), "r"(r1) : "memory");
}

#define R8(o) "%" #o "0,%" #o "1,%" #o "2,%" #o "3,%" #o "4,%" #o "5,%" #o "6,%" #o "7,%" #o "8,%" #o "9"
#define F4(d, i) "+f"(d[i]), "+f"(d[i + 1]), "+f"(d[i + 2]), "+f"(d[i + 3])
template <int TA, int SBO16>
__device__ __forceinline__ void mma152(float (&d)[76], uint32_t a16, uint32_t b16, int acc) {
    asm volatile(
        "{\n.reg .pred p;\n.reg .b64 da, db;\n"
        "setp.ne.b32 p, %78, 0;\n"
        "mov.b64 da, {%76, %80};\nmov.b64 db, {%77, 0x40000040};\n"
        "wgmma.mma_async.sync.aligned.m64n152k16.f32.bf16.bf16 "
        "{%0,%1,%2,%3,%4,%5,%6,%7,%8,%9," R8(1) "," R8(2) "," R8(3) "," R8(4) "," R8(5) "," R8(6) ",%70,%71,%72,%73,%74,%75}, "
        "da, db, p, 1, 1, %79, 0;\n}"
        : F4(d, 0), F4(d, 4), F4(d, 8), F4(d, 12), F4(d, 16), F4(d, 20), F4(d, 24), F4(d, 28), F4(d, 32), F4(d, 36), F4(d, 40), F4(d, 44),
          F4(d, 48), F4(d, 52), F4(d, 56), F4(d, 60), F4(d, 64), F4(d, 68), F4(d, 72)
        : "r"(a16), "r"(b16), "r"(acc), "n"(TA), "n"(0x40000000 | SBO16));
}
__device__ __forceinline__ void mma152_ones(float (&d)[76], uint32_t b16, int acc) {
    asm volatile(
        "{\n.reg .pred p;\n.reg .b64 db;\n"
        "setp.ne.b32 p, %78, 0;\n"
        "mov.b64 db, {%77, 0x40000040};\n"
        "wgmma.mma_async.sync.aligned.m64n152k16.f32.bf16.bf16 "
        "{%0,%1,%2,%3,%4,%5,%6,%7,%8,%9," R8(1) "," R8(2) "," R8(3) "," R8(4) "," R8(5) "," R8(6) ",%70,%71,%72,%73,%74,%75}, "
        "{%76,%76,%76,%76}, db, p, 1, 1, 0;\n}"
        : F4(d, 0), F4(d, 4), F4(d, 8), F4(d, 12), F4(d, 16), F4(d, 20), F4(d, 24), F4(d, 28), F4(d, 32), F4(d, 36), F4(d, 40), F4(d, 44),
          F4(d, 48), F4(d, 52), F4(d, 56), F4(d, 60), F4(d, 64), F4(d, 68), F4(d, 72)
        : "r"(0x3F803F80), "r"(b16), "r"(acc));
}
__device__ __forceinline__ void reg_fence(float (&d)[76]) {
#pragma unroll
    for (int i = 0; i < 76; i++) asm volatile("" : "+f"(d[i])::"memory");
}

struct Ring {
    uint32_t t6;
    __device__ __forceinline__ void adv(uint32_t n) { t6 += n; t6 = t6 >= 6 ? t6 - 6 : t6; }
    __device__ __forceinline__ uint32_t slot() const { return t6 >= 3 ? t6 - 3 : t6; }
    __device__ __forceinline__ uint32_t phase() const { return t6 >= 3 ? 1u : 0u; }
};

__device__ __forceinline__ void ex2v(float& x) { asm volatile("ex2.approx.ftz.f32 %0, %0;" : "+f"(x)); }
__device__ __forceinline__ void addv(float& a, float b) { asm volatile("add.f32 %0, %0, %1;" : "+f"(a) : "f"(b)); }
__device__ __forceinline__ uint32_t pack2v(float lo, float hi) { uint32_t r; asm volatile("cvt.rn.bf16x2.f32 %0, %1, %2;" : "=r"(r) : "f"(hi), "f"(lo)); return r; }

template <bool SCALE>
__device__ __forceinline__ void store_tile_t(const float (&d)[76], uint32_t addr, float c) {
#pragma unroll
    for (int j = 0; j < 18; j += 2) {
        const float* v = &d[4 * j];
        if (SCALE) stsm4t(addr + j * 1024, pack2(v[0] * c, v[1] * c), pack2(v[2] * c, v[3] * c), pack2(v[4] * c, v[5] * c), pack2(v[6] * c, v[7] * c));
        else stsm4t(addr + j * 1024, pack2(v[0], v[1]), pack2(v[2], v[3]), pack2(v[4], v[5]), pack2(v[6], v[7]));
    }
    if (SCALE) stsm2t(addr + 18 * 1024, pack2(d[72] * c, d[73] * c), pack2(d[74] * c, d[75] * c));
    else stsm2t(addr + 18 * 1024, pack2(d[72], d[73]), pack2(d[74], d[75]));
}

template <bool MAX>
__device__ __forceinline__ void column_reduce1(const float (&l)[38], uint32_t sbase) {
    const int tid = tid_now();
    const int lane = tid & 31, w = tid >> 5;
    auto op = [](float a, float b) { return MAX ? fmaxf(a, b) : a + b; };
    float a[20], b[10], c[5];
    const bool b4 = lane & 16, b3 = lane & 8, b2 = lane & 4;
#pragma unroll
    for (int i = 0; i < 20; i++) {
        float lo = l[i], hi = (i + 20 < 38) ? l[i + 20] : 0.f;
        a[i] = op(b4 ? hi : lo, __shfl_xor_sync(0xffffffffu, b4 ? lo : hi, 16));
    }
#pragma unroll
    for (int i = 0; i < 10; i++) b[i] = op(b3 ? a[i + 10] : a[i], __shfl_xor_sync(0xffffffffu, b3 ? a[i] : a[i + 10], 8));
#pragma unroll
    for (int i = 0; i < 5; i++) c[i] = op(b2 ? b[i + 5] : b[i], __shfl_xor_sync(0xffffffffu, b2 ? b[i] : b[i + 5], 4));
    const int c0 = (b4 ? 20 : 0) + (b3 ? 10 : 0) + (b2 ? 5 : 0);
#pragma unroll
    for (int i = 0; i < 5; i++) {
        const int ci = c0 + i;
        const int col = 8 * (ci >> 1) + 2 * (lane & 3) + (ci & 1);
        asm volatile("st.shared.f32 [%0], %1;" ::"r"(sbase + OFF_STG + (w * 160 + col) * 4), "f"(c[i]) : "memory");
    }
}
template <bool MAX>
__device__ __forceinline__ float2 column_reduce2(uint32_t sbase) {
    const int tid = tid_now();
    auto op = [](float a, float b) { return MAX ? fmaxf(a, b) : a + b; };
    float2 v[4];
#pragma unroll
    for (int k = 0; k < 4; k++)
        asm volatile("ld.shared.v2.f32 {%0,%1}, [%2];" : "=f"(v[k].x), "=f"(v[k].y) : "r"(sbase + OFF_STG + k * 640 + tid * 8) : "memory");
    return make_float2(op(op(v[0].x, v[1].x), op(v[2].x, v[3].x)), op(op(v[0].y, v[1].y), op(v[2].y, v[3].y)));
}
template <int N>
__device__ __forceinline__ void load_rl(float (&l)[N], uint32_t sbase) {
    const uint32_t a = sbase + OFF_RL + (tid_now() & 3) * 8;
#pragma unroll
    for (int c = 0; c < 19; c++) asm volatile("ld.shared.v2.f32 {%0,%1}, [%2];" : "=f"(l[2 * c]), "=f"(l[2 * c + 1]) : "r"(a + c * 32) : "memory");
}
template <int N>
__device__ __forceinline__ void store_out_main(const float (&s)[76], const float (&l)[N], uint32_t a0, uint32_t (&t)[6]) {
    float z = 0.f;
#pragma unroll
    for (int j = 0; j < 16; j += 2) {
        const float* v = &s[4 * j];
        const float* r = &l[2 * j];
        const uint32_t r0 = pack2(fmaf(v[0], r[0], z), fmaf(v[1], r[1], z)), r1 = pack2(fmaf(v[2], r[0], z), fmaf(v[3], r[1], z));
        const uint32_t r2 = pack2(fmaf(v[4], r[2], z), fmaf(v[5], r[3], z)), r3 = pack2(fmaf(v[6], r[2], z), fmaf(v[7], r[3], z));
        stsm4t(a0 + j * 1024, r0, r1, r2, r3);
        z = __uint_as_float((r0 & r1 & r2) & r3 & blockIdx.y);
    }
#pragma unroll
    for (int k = 0; k < 6; k++) t[k] = pack2(fmaf(s[64 + 2 * k], l[32 + (k >> 1) * 2], z), fmaf(s[65 + 2 * k], l[33 + (k >> 1) * 2], z));
}
__device__ __forceinline__ void store_out_tail(const uint32_t (&t)[6], uint32_t a1) {
    stsm4t(a1, t[0], t[1], t[2], t[3]);
    stsm2t(a1 + 2048, t[4], t[5]);
}

__device__ __forceinline__ uint32_t softmax_fast(float (&s)[76], float (&l)[38], uint32_t paddr, uint32_t nbar, uint32_t nphase, bool wait_pv0) {
    uint32_t ok = 0;
#pragma unroll
    for (int g = 0; g < 10; g++) {
        uint32_t r[4];
#pragma unroll
        for (int h = 0; h < 2; h++) {
            if (8 * g + 4 * h < 76) {
                float* v = &s[8 * g + 4 * h];
                ex2v(v[0]); ex2v(v[1]); ex2v(v[2]); ex2v(v[3]);
                r[2 * h] = pack2v(v[0], v[1]);
                r[2 * h + 1] = pack2v(v[2], v[3]);
                addv(v[2], v[0]); addv(v[3], v[1]);
                addv(l[4 * g + 2 * h], v[2]); addv(l[4 * g + 2 * h + 1], v[3]);
            }
        }
        if (g == 0) bar_sync_if<BAR_F, 384>(wait_pv0);
        if (g < 9) stsm4t(paddr + g * 2048, r[0], r[1], r[2], r[3]);
        else stsm2t(paddr + g * 2048, r[0], r[1]);
        if (g == 7) ok = mbar_test(nbar, nphase);
    }
    return ok;
}
__device__ __forceinline__ void softmax_nosum(float (&s)[76], uint32_t paddr) {
#pragma unroll
    for (int g = 0; g < 10; g++) {
        uint32_t r[4];
#pragma unroll
        for (int h = 0; h < 4; h++) {
            if (8 * g + 2 * h < 76) {
                ex2v(s[8 * g + 2 * h]); ex2v(s[8 * g + 2 * h + 1]);
                r[h] = pack2v(s[8 * g + 2 * h], s[8 * g + 2 * h + 1]);
            }
        }
        if (g < 9) stsm4t(paddr + g * 2048, r[0], r[1], r[2], r[3]);
        else stsm2t(paddr + g * 2048, r[0], r[1]);
    }
}
__device__ __forceinline__ void add_tile_sums(float (&l)[38], uint32_t paddr) {
#pragma unroll
    for (int g = 0; g < 10; g++) {
        uint32_t r[4];
        if (g >= CHAIN_D) paddr += __float_as_uint(l[4 * (g - CHAIN_D) + 3]) & blockIdx.y;
        if (g < 9) asm volatile("ldmatrix.sync.aligned.m8n8.x4.trans.shared.b16 {%0,%1,%2,%3}, [%4];" : "=r"(r[0]), "=r"(r[1]), "=r"(r[2]), "=r"(r[3]) : "r"(paddr + g * 2048) : "memory");
        else asm volatile("ldmatrix.sync.aligned.m8n8.x2.trans.shared.b16 {%0,%1}, [%2];" : "=r"(r[0]), "=r"(r[1]) : "r"(paddr + g * 2048) : "memory");
#pragma unroll
        for (int h = 0; h < 4; h++) {
            if (8 * g + 2 * h < 76) {
                addv(l[4 * g + (h >> 1) * 2], __uint_as_float(r[h] << 16));
                addv(l[4 * g + (h >> 1) * 2 + 1], __uint_as_float(r[h] & 0xFFFF0000u));
            }
        }
    }
}
__device__ __forceinline__ void softmax_safe(const float (&s)[76], float (&l)[38], uint32_t paddr, uint32_t maddr) {
#pragma unroll
    for (int j = 0; j < 19; j += 2) {
        uint32_t r[4];
#pragma unroll
        for (int jj = 0; jj < 2; jj++) {
            if (j + jj < 19) {
                const float* v = &s[4 * (j + jj)];
                float m0, m1;
                asm volatile("ld.shared.v2.f32 {%0,%1}, [%2];" : "=f"(m0), "=f"(m1) : "r"(maddr + (j + jj) * 32) : "memory");
                const float p0 = ex2(v[0] - m0), p1 = ex2(v[1] - m1), p2 = ex2(v[2] - m0), p3 = ex2(v[3] - m1);
                l[2 * (j + jj)] += p0; l[2 * (j + jj) + 1] += p1;
                l[2 * (j + jj)] += p2; l[2 * (j + jj) + 1] += p3;
                r[2 * jj] = pack2(p0, p1); r[2 * jj + 1] = pack2(p2, p3);
            }
        }
        if (j + 1 < 19) stsm4t(paddr + j * 1024, r[0], r[1], r[2], r[3]);
        else stsm2t(paddr + j * 1024, r[0], r[1]);
    }
}

__device__ __forceinline__ uint32_t stsm_lane_off(int tid) {
    const int lane = tid & 31, w = (tid >> 5) & 3, mi = lane >> 3, r = lane & 7;
    return ((mi >> 1) * 8 + r) * 128 + (((2 * w + (mi & 1)) ^ r) << 4);
}

template <int TA, int C>
__device__ __forceinline__ void issue_quarter(float (&s)[76], uint32_t a16) {
    if (C == 0) wg_fence();
#pragma unroll
    for (int k = 0; k < 4; k++) mma152<TA, TA ? 64 : 256>(s, a16 + (TA ? C * 512 + k * 128 : C * 64 + k * 2), S16 + C * (CH >> 4) + k * 2, C + k > 0);
}
template <int TA>
__device__ __forceinline__ void issue_s_op(float (&s)[76], uint32_t a16) {
    issue_quarter<TA, 0>(s, a16); issue_quarter<TA, 1>(s, a16); issue_quarter<TA, 2>(s, a16); issue_quarter<TA, 3>(s, a16);
    wg_commit();
}
template <int TA>
__device__ __forceinline__ void issue_rest_chasing(float (&s)[76], uint32_t a16, bool chase) {
    bar_sync_if<BAR_C + 2, 256>(chase);
    if (TA) wg_fence();
    issue_quarter<TA, 2>(s, a16);
    bar_sync_if<BAR_C + 1, 256>(chase);
    issue_quarter<TA, 1>(s, a16);
    bar_sync_if<BAR_C + 3, 256>(chase);
    issue_quarter<TA, 3>(s, a16);
    wg_commit();
}
__device__ __forceinline__ uint32_t slot16(uint32_t sl) { return S16 + ((OFF_RING + sl * TILE) >> 4); }

__device__ __forceinline__ uint32_t s_round(const uint32_t sbase, const int tid, Ring& ring, const int nu, const bool safe, const bool emit_in,
                                            const uint32_t rel0, const uint32_t rank) {
    const int lane = tid & 31;
    const uint32_t lane_off = stsm_lane_off(tid);
    float s[76], l[38];
    uint32_t bad = 0;
    ring.adv(1);
#pragma unroll 1
    for (int u = 0; u < nu; u++) {
        const bool paired = u + 1 < nu;
        uint32_t t1 = 0, t2 = 0, t3 = 0;
#pragma unroll 1
        for (int pass = safe ? 0 : 1; pass < 2; pass++) {
            const float init = pass == 0 ? -INFINITY : 0.f;
#pragma unroll
            for (int i = 0; i < 38; i++) l[i] = init;
            uint32_t sl = ring.slot();
            {
                const bool first = pass == 0 || !safe;
                bar_sync_if<BAR_C, 384>(first && u == 0);
                mbar_wait(sbase + OFF_FULL + sl * 8, ring.phase());
                bar_sync_if<BAR_C, 384>(first && u > 0);
                issue_quarter<0, 0>(s, slot16(sl));
                issue_rest_chasing<0>(s, slot16(sl), first);
                bar_arrive_if<BAR_G + 1, 256>(!safe);
                PROF(0, u * 128 + 2);
                GT(1 + u * 4);
            }
#pragma unroll 1
            for (int j = 0;; j += (j == 0 && !safe) ? 2 : 1) {
                const bool j2 = j == 2 && !safe;
                ring.adv((safe && (j == 0 || pass == 0)) ? 1 : ((j == 15 || j2) ? 3 : 2));
                const uint32_t rel = rel0 + sl * 8;
                sl = ring.slot();
                const uint32_t nbar = sbase + OFF_FULL + sl * 8, nphase = ring.phase(), na16 = slot16(sl);
                const uint32_t pa = sbase + (4 + (j & 1)) * CH + lane_off;
                wg_wait0();
                reg_fence(s);
                PROF2(0, u * 128 + j * 4 + 3);
                release_slot(rel, lane, 2);
                if (j2) {
                    bar_arrive<BAR_A, 384>();
                    bar_sync<BAR_D, 256>();
                    add_tile_sums(l, pa + CH);
                }
                uint32_t ready = 0;
                if (!safe) ready = softmax_fast(s, l, pa, nbar, nphase, j2);
                else if (pass == 1) softmax_safe(s, l, pa, sbase + OFF_RL + (tid_now() & 3) * 8);
                else {
#pragma unroll
                    for (int c = 0; c < 19; c++) {
                        l[2 * c] = fmaxf(l[2 * c], fmaxf(s[4 * c], s[4 * c + 2]));
                        l[2 * c + 1] = fmaxf(l[2 * c + 1], fmaxf(s[4 * c + 1], s[4 * c + 3]));
                    }
                }
                if (j == 15) break;
                PROF2(0, u * 128 + j * 4 + 4);
                if (!ready) mbar_wait(nbar, nphase);
                issue_s_op<0>(s, na16);
                fence_async_smem();
                bar_sync_if<BAR_A, 384>(pass == 1);
                PROF(0, u * 128 + j * 4 + 6);
            }
            TS(t1);
            fence_async_smem();
            bar_sync_if<BAR_A, 384>(pass == 1);
            TS(t2);
            if (pass == 0) {
                column_reduce1<true>(l, sbase);
                bar_sync<BAR_E, 128>();
                const float2 m = column_reduce2<true>(sbase);
                const int t = tid_now();
                if (t < 76) asm volatile("st.shared.v2.f32 [%0], {%1,%2};" ::"r"(sbase + OFF_RL + t * 8), "f"(m.x), "f"(m.y) : "memory");
                bar_sync<BAR_E, 128>();
            }
        }
#pragma unroll
        for (int i = 0; i < 38; i++) asm volatile("" : "+f"(l[i])::"memory");
        {
            const int tn = tid_now();
            const uint32_t la = sbase + 3 * CH + (tn & 31) * 128 + (((tn >> 5) ^ (tn & 7)) << 4);
#pragma unroll
            for (int j = 0; j < 16; j += 4)
                stsm4t(la + j * 1024, pack2(l[2 * j], l[2 * j + 1]), pack2(l[2 * j + 2], l[2 * j + 3]), pack2(l[2 * j + 4], l[2 * j + 5]), pack2(l[2 * j + 6], l[2 * j + 7]));
            stsm4t(la + 15 * 1024, pack2(l[30], l[31]), pack2(l[32], l[33]), pack2(l[34], l[35]), pack2(l[36], l[37]));
            fence_async_smem();
            bar_sync<BAR_E, 128>();
            wg_fence();
#pragma unroll
            for (int k = 0; k < (LSPLIT ? 4 : 2); k++) mma152_ones(s, S16 + 3 * (CH >> 4) + k * 2, k > 0);
            wg_commit();
            bar_arrive<BAR_G + 1, 256>();
            wg_wait0();
            reg_fence(s);
#pragma unroll
            for (int c = 0; c < 19; c++) {
                asm volatile("rcp.approx.ftz.f32 %0, %1;" : "=f"(l[2 * c]) : "f"(s[4 * c]));
                asm volatile("rcp.approx.ftz.f32 %0, %1;" : "=f"(l[2 * c + 1]) : "f"(s[4 * c + 1]));
            }
        }
        uint32_t tail[6] = {0, 0, 0, 0, 0, 0};
#pragma unroll 1
        for (int i = 0; i < 7; i += paired ? 1 : 2) {
            const uint32_t sl = ring.slot();
            PROF2(0, u * 128 + 64 + i * 4);
            mbar_wait(sbase + OFF_FULL + sl * 8, ring.phase());
            bar_sync_if<BAR_D, 256>(i > 0);
            bar_sync_if<BAR_C, 384>(i == 0);
            PROF2(0, u * 128 + 64 + i * 4 + 1);
            issue_quarter<1, 0>(s, slot16(sl));
            if (i == 0) {
                uint32_t acc = 0;
#pragma unroll
                for (int c = 0; c < 38; c++) {
                    asm volatile("" : "+f"(l[c]));
                    acc = max(acc, __float_as_uint(l[c]) - (90u << 23));
                }
                const uint32_t any = __any_sync(0xffffffffu, (acc >> 29) != 0) ? 1u : 0u;
                const bool emit = safe ? emit_in : any == 0;
                bad |= any << u;
                asm volatile("st.shared.u32 [%0], %1;" ::"r"(sbase + OFF_EMIT), "r"((uint32_t)emit) : "memory");
            }
            issue_rest_chasing<1>(s, slot16(sl), i == 0);
            bar_sync_if<BAR_A, 384>(paired);
            bar_arrive_if<BAR_G, 256>(!paired && i < 6);
            PROF(0, u * 128 + 64 + i * 4 + 2);
            ring.adv(paired || i < 6 ? 2 : 1);
            if (i == 0 && !paired) {
                const int tn = tid_now();
#pragma unroll
                for (int c = 0; c < 19; c++)
                    if (tn < 4) asm volatile("st.shared.v2.f32 [%0], {%1,%2};" ::"r"(sbase + OFF_RL + tn * 8 + c * 32), "f"(l[2 * c]), "f"(l[2 * c + 1]) : "memory");
                if (!safe) asm volatile("st.shared::cluster.u32 [%0], %1;" ::"r"(rel0 - OFF_EMPTY + OFF_FLAG + rank * 4), "r"(bad) : "memory");
            }
            if (paired && i > 0) {
                store_out_tail(tail, sbase + (5 - (i & 1)) * CH + 16384 + lane_off);
                fence_async_smem();
                bar_arrive<BAR_T, 160>();
            }
            bar_sync_if<BAR_K, 160>(i > 0);
            wg_wait0();
            reg_fence(s);
            PROF2(0, u * 128 + 64 + i * 4 + 3);
            release_slot(rel0 + sl * 8, lane, 2);
            bar_arrive_if<BAR_G, 256>(paired && i == 6);
            store_out_main(s, l, sbase + (paired ? OFF_STG : 4 * CH) + lane_off, tail);
            if (!paired || i == 6) store_out_tail(tail, sbase + (paired ? 5 * CH : 4 * CH + 16384) + lane_off);
            fence_async_smem();
            bar_arrive<BAR_H, 160>();
        }
    }
    asm volatile("fence.acq_rel.cluster;" ::: "memory");
    return bad;
}

struct Producer {
    Ring ring;
    int pu, pp;
    const CUtensorMap* map;
    int c0, c1, c3;
    uint32_t xdst, bytes;
    uint64_t pol;
};
constexpr uint64_t POL_FIRST = 0x12F0000000000000ull, POL_NORMAL = 0x1000000000000000ull;

__device__ __forceinline__ void next_tile(const CUtensorMap* maps, Producer& pr, const uint32_t sbase, const int nu, const bool safe, const int bh0) {
    int q = pr.pp + 1;
    q = (q == -16 && !safe) ? 0 : q;
    q += (q > 32 && pr.pu + 1 == nu) ? 1 : 0;
    const bool wrap = q >= 46;
    q = wrap ? 0 : q;
    pr.pu += wrap ? 1 : 0;
    pr.pp = q;
    q ^= ((q >> 1) == 1 && !safe) ? 1 : 0;
    const int bh = bh0 + 4 * pr.pu;
    const bool proj = q >= 32, pro = q < -16;
    const int isk = q < 0 ? 1 : (0x2AAAAAABu >> (q & 31)) & 1;
    const bool wq = pro || (proj && (q & 1)), wo = proj && !(q & 1);
    const int n = q < 0 ? (pro ? q + 23 : q + 16) : (proj ? (q - 32) >> 1 : (q + 2 * isk - 1) >> 1);
    pr.map = maps + (wq ? 3 : (wo ? 4 : 2 - isk));
    pr.c0 = wo ? n * 64 : 0;
    pr.c1 = wo ? 0 : n * 64;
    pr.c3 = (wq || wo) ? (bh + (proj && wq ? 4 : 0)) & 15 : bh;
    pr.bytes = wq ? TILE + CH : TILE;
    pr.xdst = (wq && q < 36) ? sbase + (pro ? (0x4503210 >> (4 * n)) & 7 : 4 + (n & 1)) * CH : 0;
    pr.pol = (wq || wo) ? POL_NORMAL : POL_FIRST;
}

__device__ __forceinline__ void tma_load_2d(uint32_t dst, const void* m, uint32_t bar, int c0, int c1) {
    asm volatile("cp.async.bulk.tensor.2d.shared::cluster.global.mbarrier::complete_tx::bytes [%0], [%1, {%3, %4}], [%2];" ::"r"(dst), "l"(m), "r"(bar),
                 "r"(c0), "r"(c1) : "memory");
}
__device__ __forceinline__ void tma_add_2d(const CUtensorMap* m, int c0, int c1, uint32_t src) {
    asm volatile("cp.reduce.async.bulk.tensor.2d.global.shared::cta.add.tile.bulk_group [%0, {%1, %2}], [%3];" ::"l"(m), "r"(c0), "r"(c1), "r"(src) : "memory");
    asm volatile("cp.async.bulk.commit_group;" ::: "memory");
}

__device__ __forceinline__ void load_tile(const CUtensorMap* maps, Producer& pr, const uint32_t sbase, const int nu, const int row0, const uint32_t rank) {
    if (pr.pu >= nu) return;
    const uint32_t sl = pr.ring.slot();
    const uint32_t full = sbase + OFF_FULL + sl * 8;
    const uint32_t dst = sbase + OFF_RING + sl * TILE + rank * 16384;
    mbar_wait(full + (OFF_EMPTY - OFF_FULL), pr.ring.phase() ^ 1);
    if (elect_one()) {
        asm volatile("mbarrier.arrive.expect_tx.shared::cta.b64 _, [%0], %1;" ::"r"(full), "r"(pr.bytes) : "memory");
        asm volatile(
            "cp.async.bulk.tensor.5d.shared::cluster.global.mbarrier::complete_tx::bytes.multicast::cluster.L2::cache_hint [%0], [%1, {%3, %5, %5, %4, %6}], [%2], %7, %8;" ::"r"(dst),
            "l"(pr.map), "r"(full), "r"(pr.c0), "r"((pr.c1 >> 3) + 4 * rank), "r"(0), "r"(pr.c3), "h"((uint16_t)3), "l"(pr.pol) : "memory");
        if (pr.xdst) tma_load_2d(pr.xdst, maps, full, pr.c1, row0);
    }
    pr.ring.adv(1);
}
#define NEXT() next_tile(maps, pr, sbase, nu, safe, bh0)
#define LOAD() load_tile(maps, pr, sbase, nu, row0, rank)

__device__ __forceinline__ void emit_tile(const Params& p, const uint32_t sbase, const int i, const uint32_t a0, const uint32_t a1, const int br,
                                          const int row0) {
    uint32_t emit;
    asm volatile("ld.shared.u32 %0, [%1];" : "=r"(emit) : "r"(sbase + OFF_EMIT) : "memory");
    if (elect_one() && emit) {
        if (a1) tma_add_2d(&p.maps[11], br * 448 + i * 64, row0 + 128, a1);
        if (a0) tma_add_2d(&p.maps[10], br * 448 + i * 64, row0, a0);
    }
    __syncwarp();
}

template <int OID>
__device__ __forceinline__ void o_round(const Params& p, const uint32_t sbase, const int tid, const int warp, Ring& ring, Producer& pr, const int nu,
                                        const bool safe, const uint32_t rel0, const int br, const int bh0, const int row0, const uint32_t rank) {
    const int lane = tid & 31;
    const bool lead = (warp & 3) == 1;
    const CUtensorMap* maps = &p.maps[br * 5];
    float o0[76], o1[76];
    if (OID == 0 && lead) {
        pr.pu = 0; pr.pp = safe ? -24 : -21;
        if (safe) {
#pragma unroll 1
            for (int i = 0; i < 3; i++) { NEXT(); LOAD(); }
        }
    }
#pragma unroll 1
    for (int ph = 0; ph < 2 * nu; ph++) {
        const bool isq = (ph & 1) == 0, pro = ph == 0;
        const int nops = isq ? 7 : 16;
        if (OID == 1) {
            if (!isq && !safe) {
                Ring kr = ring; kr.adv(4);
                const uint32_t ksl = kr.slot(), k16 = slot16(ksl);
                mbar_wait(sbase + OFF_FULL + ksl * 8, kr.phase());
                bar_sync_if_after<BAR_G + 1, 256>(true, k16, k16);
                issue_s_op<0>(o0, k16);
                bar_arrive<BAR_A, 384>();
                if (ph > 1) {
                    if (lead) {
                        bar_sync<BAR_H, 160>();
                        emit_tile(p, sbase, 6, sbase + OFF_STG, sbase + 5 * CH, br, row0);
                        asm volatile("cp.async.bulk.wait_group.read 1;" ::: "memory");
                        __syncwarp();
                    }
                    bar_sync<BAR_K, 128>();
                }
                const uint32_t pa = sbase + 5 * CH + stsm_lane_off(tid_now());
                wg_wait0();
                reg_fence(o0);
                release_slot(rel0 + ksl * 8, lane, 2);
                softmax_nosum(o0, pa);
                fence_async_smem();
                bar_arrive<BAR_D, 256>();
            } else {
                asm volatile("cp.async.bulk.wait_group.read 0;" ::: "memory");
                __syncwarp();
                bar_arrive_if<BAR_A, 384>(!pro);
            }
            if (ph == 2 && lead) {
                asm volatile(
                    "{\n.reg .pred p;\n.reg .u32 c, v, t;\nmov.u32 c, 0;\n"
                    "ld.shared.u32 t, [%1];\n"
                    "Z_LOOP:\n"
                    "ld.acquire.gpu.global.u32 v, [%0];\n"
                    "sub.u32 v, v, t;\n"
                    "setp.ge.s32 p, v, 0;\n"
                    "vote.sync.all.pred p, p, 0xffffffff;\n"
                    "@p bra.uni Z_DONE;\n"
                    "add.u32 c, c, 1;\n"
                    "setp.lt.u32 p, c, 0x1000000;\n"
                    "@p bra.uni Z_LOOP;\n"
                    "trap;\n"
                    "Z_DONE:\n}" ::"l"(&g_zero_cnt), "r"(sbase + OFF_ZT) : "memory");
            }
        } else if (!pro && lead) {
            const int n = isq ? 1 : (safe ? 18 : 3);
#pragma unroll 1
            for (int i = 0; i < n; i++) { NEXT(); LOAD(); }
        }
#pragma unroll 1
        for (int i = 0; i < nops; i++) {
            const uint32_t sl = ring.slot();
            const uint32_t a16 = slot16(sl) + OID * 128;
            const uint32_t bi = pro ? (0x4503210 >> (4 * i)) & 7 : 4 + (i & 1);
            const uint32_t b16 = S16 + bi * (CH >> 4);
            const bool last = i + 1 == nops;
            const bool oo = i == 14 || (i == 0 && !isq && !safe);
            PROF2(1 + OID, ph * 64 + i * 4);
            const uint32_t fphase = ring.phase();
            uint32_t n = 2;
            if (pro || oo) n = 1;
            if (last) n = isq ? (safe ? 1 : 4) : 2;
            ring.adv(n);
            if (OID == 0) {
                bar_sync_if<BAR_A, 384>(!pro && i != 15);
                bar_sync_if<BAR_F, 256>(pro && i > 0);
                bar_arrive_if<BAR_F, 384>(i == 1 && !isq && !safe);
            } else {
                bar_sync_if<BAR_B, 256>(safe);
            }
            PROF2(1 + OID, ph * 64 + i * 4 + 1);
            mbar_wait(sbase + OFF_FULL + sl * 8, fphase);
            if (OID == 0) bar_sync_if_after<BAR_A, 384>(i == 15, a16, b16);
            else {
                bar_sync_if<BAR_G + 1, 256>(i == 15);
                bar_sync_if_after<BAR_B, 256>(!safe, a16, b16);
            }
            uint32_t ta = 0, tb = 0, tc = 0, td = 0, te = 0, tf = 0; TS(ta);
            wg_fence();
#pragma unroll
            for (int k = 0; k < 4; k++) mma152<1, 256>(o0, a16 + k * 512, b16 + k * 2, k > 0 || i > 0);
            wg_commit();
#pragma unroll
            for (int k = 0; k < 4; k++) mma152<1, 256>(o1, a16 + 64 + k * 512, b16 + k * 2, k > 0 || i > 0);
            wg_commit();
            if (OID == 0) {
                bar_arrive<BAR_B, 256>();
                if (lead && !(pro && i == 0) && !last) { NEXT(); LOAD(); }
            } else {
                bar_arrive_if<BAR_F, 256>(pro && !last);
                bar_arrive_if<BAR_D, 256>(isq && !pro && !last);
                bar_arrive_if<BAR_A, 384>(oo);
                if (last && (warp & 3) == 2) {
                    int phv;
                    asm volatile("mov.u32 %0, %1;" : "=r"(phv) : "r"(ph));
                    const bool k1 = (phv & 1) == 0, wq0 = !k1 && phv + 1 < 2 * nu;
                    const int bh = bh0 + 4 * (phv >> 1);
                    Producer pr;
                    pr.pu = 0;
                    pr.ring.t6 = sl + 3 * fphase; pr.ring.adv(2);
                    pr.map = maps + (k1 ? 1 : (wq0 ? 3 : 4));
                    pr.c0 = (k1 || wq0) ? 0 : 64;
                    pr.c1 = k1 ? 64 : 0;
                    pr.c3 = k1 ? bh : (bh + (wq0 ? 4 : 0)) & 15;
                    pr.bytes = wq0 ? TILE + CH : TILE;
                    pr.xdst = wq0 ? sbase + 4 * CH : 0;
                    pr.pol = k1 ? POL_FIRST : POL_NORMAL;
                    LOAD();
                }
                if (lead && isq && !pro && !last) {
                    if (i > 0) {
                        asm volatile("cp.async.bulk.wait_group.read 0;" ::: "memory");
                        if (elect_one()) tma_load_2d(sbase + (5 - (i & 1)) * CH, maps, sbase + OFF_FULL + ring.slot() * 8, (i + 1) * 64, row0);
                        __syncwarp();
                    }
                    bar_sync<BAR_H, 160>();
                    emit_tile(p, sbase, i, sbase + OFF_STG, 0, br, row0);
                }
            }
            PROF2(1 + OID, ph * 64 + i * 4 + 2);
            TS(tb);
            if (last) {
                const uint32_t qa = sbase + OID * 2 * CH + stsm_lane_off(tid_now());
                const float c = 0.0625f * 1.4426950408889634f;
                if (OID == 0) {
                    bar_sync_if<BAR_G, 256>(isq && !pro);
                    wg_wait1();
                } else {
                    bar_sync<BAR_C, 384>();
                    wg_wait1();
                }
                reg_fence(o0);
                TS(tc);
                if (isq) store_tile_t<true>(o0, qa, c); else store_tile_t<false>(o0, qa, c);
                fence_async_smem();
                bar_arrive<BAR_C + 2 * OID, OID == 0 ? 384 : 256>();
                TS(td);
                wg_wait0();
                reg_fence(o1);
                TS(te);
                release_slot(rel0 + sl * 8, lane, 1);
                if (isq) store_tile_t<true>(o1, qa + CH, c); else store_tile_t<false>(o1, qa + CH, c);
                fence_async_smem();
                bar_arrive<BAR_C + 2 * OID + 1, 256>();
                PROF2(1 + OID, ph * 64 + i * 4 + 3);
                if (OID == 0) { pr.pp += (!isq && ph + 1 == 2 * nu) ? 2 : 1; pr.ring.adv(1); }
            } else {
                wg_wait0();
                reg_fence(o0);
                reg_fence(o1);
                PROF2(1 + OID, ph * 64 + i * 4 + 3);
                release_slot(rel0 + sl * 8, lane, 1);
                if (OID == 0) {
                    if (lead && !pro && !oo) { NEXT(); LOAD(); }
                } else {
                    bar_arrive_if<BAR_A, 384>(!pro && !oo);
                    bar_arrive_if<BAR_F, 384>(oo && i == 0);
                }
            }
            if (OID == 1 && lead && isq && !pro && !last) {
                asm volatile("cp.async.bulk.wait_group.read 0;" ::: "memory");
                __syncwarp();
                bar_arrive<BAR_K, 160>();
                bar_sync<BAR_T, 160>();
                emit_tile(p, sbase, i, 0, sbase + (4 + (i & 1)) * CH + 16384, br, row0);
            }
        }
    }
    if (OID == 0) {
        if (lead) { NEXT(); LOAD(); }
#pragma unroll 1
        for (int i = 1; i < 7; i += 2) {
            const uint32_t sl = ring.slot();
            bar_sync<BAR_G, 256>();
            mbar_wait(sbase + OFF_FULL + sl * 8, ring.phase());
            issue_s_op<1>(o0, slot16(sl));
            bar_arrive<BAR_D, 256>();
            if (lead) { NEXT(); LOAD(); NEXT(); }
            ring.adv(2);
            bar_sync<BAR_K + 1, 160>();
            load_rl(o1, sbase);
            wg_wait0();
            reg_fence(o0);
            release_slot(rel0 + sl * 8, lane, 2);
            if (lead) LOAD();
            const uint32_t a = sbase + 5 * CH + stsm_lane_off(tid_now());
            uint32_t tail[6];
            store_out_main(o0, o1, a, tail);
            store_out_tail(tail, a + 16384);
            fence_async_smem();
            bar_arrive<BAR_H + 1, 160>();
        }
    } else if (lead) {
#pragma unroll 1
        for (int i = 0; i < 7; i++) {
            bar_sync_if<BAR_H, 160>(!(i & 1));
            bar_sync_if<BAR_H + 1, 160>(i & 1);
            const uint32_t a = sbase + (4 + (i & 1)) * CH;
            emit_tile(p, sbase, i, a, a + 16384, br, row0);
            asm volatile("cp.async.bulk.wait_group.read 2;" ::: "memory");
            __syncwarp();
            bar_arrive_if<BAR_K, 160>(i & 1);
            bar_arrive_if<BAR_K + 1, 160>(!(i & 1) && i < 6);
        }
        asm volatile("cp.async.bulk.wait_group.read 0;" ::: "memory");
    }
}

__device__ __forceinline__ uint32_t read_redo(uint32_t sbase) {
    uint32_t a, b;
    asm volatile("ld.shared.v2.u32 {%0,%1}, [%2];" : "=r"(a), "=r"(b) : "r"(sbase + OFF_FLAG) : "memory");
    return __shfl_sync(0xffffffffu, a | b, 0);
}

template <int OID>
__device__ __forceinline__ void o_role(const Params& p, const uint32_t sbase, const int tid, const int warp, const uint32_t rel0, const int br,
                                       const int bh_first, const int row0, const uint32_t rank) {
    Ring ring; ring.t6 = 0;
    Producer pr; pr.ring.t6 = 3;
    uint32_t redo = 0;
#pragma unroll 1
    for (int r = -1; r < 4; r++) {
        if (r < 0 || ((redo >> r) & 1)) {
            o_round<OID>(p, sbase, tid, warp, ring, pr, r < 0 ? 4 : 1, r >= 0, rel0, br, r < 0 ? bh_first : bh_first + 4 * r, row0, rank);
            cluster_sync_relaxed();
            if (r < 0) redo = read_redo(sbase);
        }
    }
}

__global__ void __cluster_dims__(2, 1, 1) __launch_bounds__(384, 1) fused_mha_kernel(const __grid_constant__ Params p) {
    extern __shared__ __align__(1024) uint8_t smem_raw[];
    const uint32_t sbase = (uint32_t)__cvta_generic_to_shared(smem_raw);
    const int warp = __shfl_sync(0xffffffffu, threadIdx.x >> 5, 0);
    const int tid = threadIdx.x & 127;
    const uint32_t rank = blockIdx.x & 1;
    const int cl = (int)(blockIdx.x >> 1) - 2;
    if (cl < 0) {
        uint4* z = reinterpret_cast<uint4*>(p.out) + blockIdx.x * 68096;
#pragma unroll 1
        for (int i = threadIdx.x; i < 68096; i += 384) z[i] = make_uint4(0, 0, 0, 0);
        asm volatile("fence.proxy.async;" ::: "memory");
        __threadfence();
        __syncthreads();
        if (threadIdx.x == 0) atomicAdd(&g_zero_cnt, 1u);
        return;
    }
    const int bb = cl >> 2;
    const int br = bb >> 3;
    const int bh_first = (bb & 7) * 16 + (cl & 3);
    const int row0 = (bb & 7) * 304 + rank * NQ;
    if (warp == 0) {
        if (elect_one()) {
#pragma unroll
            for (int i = 0; i < 3; i++) {
                asm volatile("mbarrier.init.shared::cta.b64 [%0], 1;" ::"r"(sbase + OFF_FULL + i * 8) : "memory");
                asm volatile("mbarrier.init.shared::cta.b64 [%0], 16;" ::"r"(sbase + OFF_EMPTY + i * 8) : "memory");
            }
            asm volatile("fence.mbarrier_init.release.cluster;" ::: "memory");
            fence_async_smem();
#pragma unroll
            for (int i = 0; i < 3; i++) {
                const uint32_t full = sbase + OFF_FULL + i * 8;
                asm volatile("mbarrier.arrive.expect_tx.shared::cta.b64 _, [%0], %1;" ::"r"(full), "r"(TILE + CH) : "memory");
#pragma unroll
                for (int h = 0; h < 2; h++)
                    asm volatile("cp.async.bulk.tensor.5d.shared::cluster.global.mbarrier::complete_tx::bytes [%0], [%1, {%3, %3, %3, %4, %5}], [%2];" ::"r"(
                                     sbase + OFF_RING + i * TILE + h * 16384),
                                 "l"(&p.maps[br * 5 + 3]), "r"(full), "r"(0), "r"(i * 8 + 4 * h), "r"(cl & 3) : "memory");
                tma_load_2d(sbase + i * CH, &p.maps[br * 5], full, i * 64, row0);
            }
        }
    }
    asm volatile("{\n.reg .pred p;\nsetp.ne.u32 p, %0, 1024;\n@p trap;\n}" ::"r"(sbase & 0x3FFFF));
    uint32_t rel0;
    asm volatile("mapa.shared::cluster.u32 %0, %1, %2;" : "=r"(rel0) : "r"(sbase + OFF_EMPTY), "r"(threadIdx.x & 1));
    cluster_sync_relaxed();

    if (warp < 4) {
        asm volatile("setmaxnreg.dec.sync.aligned.u32 136;");
        if (warp == 0) {
            if (elect_one()) {
                const uint32_t e = g_epoch[blockIdx.x - 4] + 1;
                g_epoch[blockIdx.x - 4] = e;
                asm volatile("st.shared.u32 [%0], %1;" ::"r"(sbase + OFF_ZT), "r"(4 * e) : "memory");
            }
            __syncwarp();
        }
        Ring ring; ring.t6 = 0;
        uint32_t redo = 0, bad = 0;
#pragma unroll 1
        for (int r = -1; r < 4; r++) {
            if (r < 0 || ((redo >> r) & 1)) {
                const uint32_t b = s_round(sbase, tid, ring, r < 0 ? 4 : 1, r >= 0, r >= 0 && ((bad >> r) & 1), rel0, rank);
                cluster_sync_relaxed();
                if (r < 0) { bad = b; redo = read_redo(sbase); }
            }
        }
    } else {
        asm volatile("setmaxnreg.inc.sync.aligned.u32 184;");
        if (warp < 8) o_role<0>(p, sbase, tid, warp, rel0, br, bh_first, row0, rank);
        else o_role<1>(p, sbase, tid, warp, rel0, br, bh_first, row0, rank);
    }
}

typedef CUresult (*EncodeFn)(CUtensorMap*, CUtensorMapDataType, cuuint32_t, void*, const cuuint64_t*, const cuuint64_t*, const cuuint32_t*,
                             const cuuint32_t*, CUtensorMapInterleave, CUtensorMapSwizzle, CUtensorMapL2promotion, CUtensorMapFloatOOBfill);

void encode(EncodeFn fn, CUtensorMap* m, void* ptr, int rank, uint64_t d0, uint64_t d1, uint64_t d3, uint64_t d4, uint64_t s1, uint64_t s2,
            uint64_t s3, uint64_t s4, uint32_t b1) {
    cuuint64_t dims[5] = {d0, d1, 4, d3, d4};
    cuuint64_t strides[4] = {s1, s2, s3, s4};
    cuuint32_t box[5] = {64, b1, 4, 4, 1};
    cuuint32_t es[5] = {1, 1, 1, 1, 1};
    fn(m, CU_TENSOR_MAP_DATA_TYPE_BFLOAT16, rank, ptr, dims, strides, box, es, CU_TENSOR_MAP_INTERLEAVE_NONE, CU_TENSOR_MAP_SWIZZLE_128B,
       PROMO, CU_TENSOR_MAP_FLOAT_OOB_FILL_NONE);
}

}

extern "C" void kernel_launch(void* const* d_in, const int* in_sizes, int n_in, void* d_out, int out_size) {
    (void)in_sizes; (void)n_in; (void)out_size;
    static EncodeFn fn = nullptr;
    if (!fn) {
        void* f = nullptr;
        cudaDriverEntryPointQueryResult q;
        cudaGetDriverEntryPoint("cuTensorMapEncodeTiled", &f, cudaEnableDefault, &q);
        fn = (EncodeFn)f;
        cudaFuncSetAttribute(fused_mha_kernel, cudaFuncAttributeMaxDynamicSharedMemorySize, SMEM_BYTES);
    }
    Params p;
    for (int br = 0; br < 2; br++) {
        void* const* in = d_in + br * 5;
        CUtensorMap* m = p.maps + br * 5;
        encode(fn, m + 0, in[0], 2, 448, 2432, 1, 1, 896, 0, 0, 0, NQ);
        encode(fn, m + 1, in[1], 5, 64, 8, 128, 128, 512, 128, 4096, 524288, 8);
        encode(fn, m + 2, in[2], 5, 64, 8, 128, 128, 512, 128, 4096, 524288, 8);
        encode(fn, m + 3, in[3], 5, 64, 8, 56, 16, 8192, 128, 65536, 512, 8);
        encode(fn, m + 4, in[4], 5, 448, 8, 8, 16, 896, 8 * 896, 32 * 896, 256 * 896, 8);
    }
    encode(fn, p.maps + 10, d_out, 2, 896, 2432, 1, 1, 1792, 0, 0, 0, 128);
    encode(fn, p.maps + 11, d_out, 2, 896, 2432, 1, 1, 1792, 0, 0, 0, 24);
    p.out = (__nv_bfloat16*)d_out;
    fused_mha_kernel<<<132, 384, SMEM_BYTES>>>(p);
}
```

```cpp
#include <cuda_runtime.h>
#include <cuda_bf16.h>
#include <cuda.h>
#include <stdint.h>

namespace {

constexpr int NQ = 152;
constexpr uint32_t CH = 19456;
constexpr uint32_t OFF_RING = 6 * CH;
constexpr uint32_t TILE = 32768;
constexpr uint32_t OFF_STG = OFF_RING + 3 * TILE;
constexpr uint32_t OFF_MISC = OFF_STG + 16384;
constexpr uint32_t OFF_FULL = OFF_MISC;
constexpr uint32_t OFF_EMPTY = OFF_MISC + 32;
constexpr uint32_t OFF_FLAG = OFF_MISC + 64;
constexpr uint32_t OFF_EMIT = OFF_MISC + 72;
constexpr uint32_t OFF_ZT = OFF_MISC + 76;
constexpr uint32_t OFF_FBAR = OFF_MISC + 80;
constexpr uint32_t OFF_RL = OFF_MISC + 128;
constexpr uint32_t SMEM_BYTES = OFF_MISC + 1024;
constexpr uint32_t S16 = 1024 >> 4;

constexpr int BAR_T = 0, BAR_A = 1, BAR_B = 2, BAR_D = 3, BAR_E = 4, BAR_F = 5, BAR_G = 6  , BAR_C = 8  , BAR_H = 12  ,
              BAR_K = 14  ;

#define CHAIN_D 2
#define PROMO CU_TENSOR_MAP_L2_PROMOTION_NONE
#define LSPLIT 0
struct Params {
    CUtensorMap maps[12];
    __nv_bfloat16* out;
};

__device__ unsigned int g_zero_cnt;
__device__ unsigned int g_epoch[128];
#define PROF(role, idx) do {} while (0)
#define GT(idx) do {} while (0)
#define TS(v) do {} while (0)
#define PROF2(role, idx) do {} while (0)

__device__ __forceinline__ void wg_fence() { asm volatile("wgmma.fence.sync.aligned;" ::: "memory"); }
__device__ __forceinline__ void wg_commit() { asm volatile("wgmma.commit_group.sync.aligned;" ::: "memory"); }
__device__ __forceinline__ void wg_wait0() { asm volatile("wgmma.wait_group.sync.aligned 0;" ::: "memory"); }
__device__ __forceinline__ void wg_wait1() { asm volatile("wgmma.wait_group.sync.aligned 1;" ::: "memory"); }
__device__ __forceinline__ void fence_async_smem() { asm volatile("fence.proxy.async.shared::cta;" ::: "memory"); }

template <int ID, int N> __device__ __forceinline__ void bar_sync() { asm volatile("bar.sync %0, %1;" ::"n"(ID), "n"(N) : "memory"); }
template <int ID, int N> __device__ __forceinline__ void bar_arrive() { asm volatile("bar.arrive %0, %1;" ::"n"(ID), "n"(N) : "memory"); }
template <int ID, int N> __device__ __forceinline__ void bar_sync_if(bool c) {
    asm volatile("{\n.reg .pred p;\nsetp.ne.b32 p, %0, 0;\n@p bar.sync %1, %2;\n}" ::"r"((int)c), "n"(ID), "n"(N) : "memory");
}
template <int ID, int N> __device__ __forceinline__ void bar_sync_if_after(bool c, uint32_t a, uint32_t b) {
    asm volatile("{\n.reg .pred p;\nsetp.ne.b32 p, %0, 0;\nsetp.ne.and.b32 p, %3, 0, p;\nsetp.ne.and.b32 p, %4, 0, p;\n@p bar.sync %1, %2;\n}" ::"r"((int)c),
                 "n"(ID), "n"(N), "r"(a), "r"(b) : "memory");
}
template <int ID, int N> __device__ __forceinline__ void bar_arrive_if(bool c) {
    asm volatile("{\n.reg .pred p;\nsetp.ne.b32 p, %0, 0;\n@p bar.arrive %1, %2;\n}" ::"r"((int)c), "n"(ID), "n"(N) : "memory");
}
__device__ __forceinline__ void cluster_sync_relaxed() {
    __syncwarp();
    asm volatile("barrier.cluster.arrive.relaxed.aligned;\nbarrier.cluster.wait.acquire.aligned;" ::: "memory");
}
__device__ __forceinline__ bool elect_one() {
    uint32_t p;
    asm volatile("{\n.reg .pred p;\nelect.sync _|p, 0xffffffff;\nselp.u32 %0, 1, 0, p;\n}" : "=r"(p));
    return p != 0;
}
__device__ __forceinline__ void mbar_wait(uint32_t bar, uint32_t parity) {
    asm volatile(
        "{\n.reg .pred p;\n.reg .u32 c;\nmov.u32 c, 0;\n"
        "W_LOOP:\n"
        "mbarrier.try_wait.parity.shared::cta.b64 p, [%0], %1;\n"
        "@p bra W_DONE;\n"
        "add.u32 c, c, 1;\n"
        "setp.lt.u32 p, c, 0x400000;\n"
        "@p bra W_LOOP;\n"
        "trap;\n"
        "W_DONE:\n}" ::"r"(bar), "r"(parity) : "memory");
}
__device__ __forceinline__ uint32_t mbar_test(uint32_t bar, uint32_t parity) {
    uint32_t ok;
    asm volatile("{\n.reg .pred p;\nmbarrier.test_wait.parity.shared::cta.b64 p, [%1], %2;\nselp.u32 %0, 1, 0, p;\n}" : "=r"(ok) : "r"(bar), "r"(parity) : "memory");
    return ok;
}
__device__ __forceinline__ void release_slot(uint32_t mapped_bar, int lane, uint32_t cnt) {
    asm volatile("{\n.reg .pred p;\nsetp.lt.s32 p, %1, 2;\n@p mbarrier.arrive.shared::cluster.b64 _, [%0], %2;\n}" ::"r"(mapped_bar),
                 "r"(lane), "r"(cnt) : "memory");
}
__device__ __forceinline__ int tid_now() { int t; asm volatile("mov.u32 %0, %%tid.x;" : "=r"(t)); return t & 127; }
__device__ __forceinline__ float ex2(float x) { float y; asm("ex2.approx.ftz.f32 %0, %1;" : "=f"(y) : "f"(x)); return y; }
__device__ __forceinline__ uint32_t pack2(float lo, float hi) { uint32_t r; asm("cvt.rn.bf16x2.f32 %0, %1, %2;" : "=r"(r) : "f"(hi), "f"(lo)); return r; }
__device__ __forceinline__ void stsm4t(uint32_t a, uint32_t r0, uint32_t r1, uint32_t r2, uint32_t r3) {
    asm volatile("stmatrix.sync.aligned.m8n8.x4.trans.shared.b16 [%0], {%1,%2,%3,%4};" ::"r"(a), "r"(r0), "r"(r1), "r"(r2), "r"(r3) : "memory");
}
__device__ __forceinline__ void stsm2t(uint32_t a, uint32_t r0, uint32_t r1) {
    asm volatile("stmatrix.sync.aligned.m8n8.x2.trans.shared.b16 [%0], {%1,%2};" ::"r"(a), "r"(r0), "r"(r1) : "memory");
}

#define R8(o) "%" #o "0,%" #o "1,%" #o "2,%" #o "3,%" #o "4,%" #o "5,%" #o "6,%" #o "7,%" #o "8,%" #o "9"
#define F4(d, i) "+f"(d[i]), "+f"(d[i + 1]), "+f"(d[i + 2]), "+f"(d[i + 3])
template <int TA, int SBO16>
__device__ __forceinline__ void mma152(float (&d)[76], uint32_t a16, uint32_t b16, int acc) {
    asm volatile(
        "{\n.reg .pred p;\n.reg .b64 da, db;\n"
        "setp.ne.b32 p, %78, 0;\n"
        "mov.b64 da, {%76, %80};\nmov.b64 db, {%77, 0x40000040};\n"
        "wgmma.mma_async.sync.aligned.m64n152k16.f32.bf16.bf16 "
        "{%0,%1,%2,%3,%4,%5,%6,%7,%8,%9," R8(1) "," R8(2) "," R8(3) "," R8(4) "," R8(5) "," R8(6) ",%70,%71,%72,%73,%74,%75}, "
        "da, db, p, 1, 1, %79, 0;\n}"
        : F4(d, 0), F4(d, 4), F4(d, 8), F4(d, 12), F4(d, 16), F4(d, 20), F4(d, 24), F4(d, 28), F4(d, 32), F4(d, 36), F4(d, 40), F4(d, 44),
          F4(d, 48), F4(d, 52), F4(d, 56), F4(d, 60), F4(d, 64), F4(d, 68), F4(d, 72)
        : "r"(a16), "r"(b16), "r"(acc), "n"(TA), "n"(0x40000000 | SBO16));
}
__device__ __forceinline__ void mma152_ones(float (&d)[76], uint32_t b16, int acc) {
    asm volatile(
        "{\n.reg .pred p;\n.reg .b64 db;\n"
        "setp.ne.b32 p, %78, 0;\n"
        "mov.b64 db, {%77, 0x40000040};\n"
        "wgmma.mma_async.sync.aligned.m64n152k16.f32.bf16.bf16 "
        "{%0,%1,%2,%3,%4,%5,%6,%7,%8,%9," R8(1) "," R8(2) "," R8(3) "," R8(4) "," R8(5) "," R8(6) ",%70,%71,%72,%73,%74,%75}, "
        "{%76,%76,%76,%76}, db, p, 1, 1, 0;\n}"
        : F4(d, 0), F4(d, 4), F4(d, 8), F4(d, 12), F4(d, 16), F4(d, 20), F4(d, 24), F4(d, 28), F4(d, 32), F4(d, 36), F4(d, 40), F4(d, 44),
          F4(d, 48), F4(d, 52), F4(d, 56), F4(d, 60), F4(d, 64), F4(d, 68), F4(d, 72)
        : "r"(0x3F803F80), "r"(b16), "r"(acc));
}
__device__ __forceinline__ void reg_fence(float (&d)[76]) {
#pragma unroll
    for (int i = 0; i < 76; i++) asm volatile("" : "+f"(d[i])::"memory");
}

struct Ring {
    uint32_t t6;
    __device__ __forceinline__ void adv(uint32_t n) { t6 += n; t6 = t6 >= 6 ? t6 - 6 : t6; }
    __device__ __forceinline__ uint32_t slot() const { return t6 >= 3 ? t6 - 3 : t6; }
    __device__ __forceinline__ uint32_t phase() const { return t6 >= 3 ? 1u : 0u; }
};

__device__ __forceinline__ void ex2v(float& x) { asm volatile("ex2.approx.ftz.f32 %0, %0;" : "+f"(x)); }
__device__ __forceinline__ void addv(float& a, float b) { asm volatile("add.f32 %0, %0, %1;" : "+f"(a) : "f"(b)); }
__device__ __forceinline__ uint32_t pack2v(float lo, float hi) { uint32_t r; asm volatile("cvt.rn.bf16x2.f32 %0, %1, %2;" : "=r"(r) : "f"(hi), "f"(lo)); return r; }

template <bool SCALE>
__device__ __forceinline__ void store_tile_t(const float (&d)[76], uint32_t addr, float c) {
#pragma unroll
    for (int j = 0; j < 18; j += 2) {
        const float* v = &d[4 * j];
        if (SCALE) stsm4t(addr + j * 1024, pack2(v[0] * c, v[1] * c), pack2(v[2] * c, v[3] * c), pack2(v[4] * c, v[5] * c), pack2(v[6] * c, v[7] * c));
        else stsm4t(addr + j * 1024, pack2(v[0], v[1]), pack2(v[2], v[3]), pack2(v[4], v[5]), pack2(v[6], v[7]));
    }
    if (SCALE) stsm2t(addr + 18 * 1024, pack2(d[72] * c, d[73] * c), pack2(d[74] * c, d[75] * c));
    else stsm2t(addr + 18 * 1024, pack2(d[72], d[73]), pack2(d[74], d[75]));
}

template <bool MAX>
__device__ __forceinline__ void column_reduce1(const float (&l)[38], uint32_t sbase) {
    const int tid = tid_now();
    const int lane = tid & 31, w = tid >> 5;
    auto op = [](float a, float b) { return MAX ? fmaxf(a, b) : a + b; };
    float a[20], b[10], c[5];
    const bool b4 = lane & 16, b3 = lane & 8, b2 = lane & 4;
#pragma unroll
    for (int i = 0; i < 20; i++) {
        float lo = l[i], hi = (i + 20 < 38) ? l[i + 20] : 0.f;
        a[i] = op(b4 ? hi : lo, __shfl_xor_sync(0xffffffffu, b4 ? lo : hi, 16));
    }
#pragma unroll
    for (int i = 0; i < 10; i++) b[i] = op(b3 ? a[i + 10] : a[i], __shfl_xor_sync(0xffffffffu, b3 ? a[i] : a[i + 10], 8));
#pragma unroll
    for (int i = 0; i < 5; i++) c[i] = op(b2 ? b[i + 5] : b[i], __shfl_xor_sync(0xffffffffu, b2 ? b[i] : b[i + 5], 4));
    const int c0 = (b4 ? 20 : 0) + (b3 ? 10 : 0) + (b2 ? 5 : 0);
#pragma unroll
    for (int i = 0; i < 5; i++) {
        const int ci = c0 + i;
        const int col = 8 * (ci >> 1) + 2 * (lane & 3) + (ci & 1);
        asm volatile("st.shared.f32 [%0], %1;" ::"r"(sbase + OFF_STG + (w * 160 + col) * 4), "f"(c[i]) : "memory");
    }
}
template <bool MAX>
__device__ __forceinline__ float2 column_reduce2(uint32_t sbase) {
    const int tid = tid_now();
    auto op = [](float a, float b) { return MAX ? fmaxf(a, b) : a + b; };
    float2 v[4];
#pragma unroll
    for (int k = 0; k < 4; k++)
        asm volatile("ld.shared.v2.f32 {%0,%1}, [%2];" : "=f"(v[k].x), "=f"(v[k].y) : "r"(sbase + OFF_STG + k * 640 + tid * 8) : "memory");
    return make_float2(op(op(v[0].x, v[1].x), op(v[2].x, v[3].x)), op(op(v[0].y, v[1].y), op(v[2].y, v[3].y)));
}
template <int N>
__device__ __forceinline__ void load_rl(float (&l)[N], uint32_t sbase) {
    const uint32_t a = sbase + OFF_RL + (tid_now() & 3) * 8;
#pragma unroll
    for (int c = 0; c < 19; c++) asm volatile("ld.shared.v2.f32 {%0,%1}, [%2];" : "=f"(l[2 * c]), "=f"(l[2 * c + 1]) : "r"(a + c * 32) : "memory");
}
template <int N>
__device__ __forceinline__ void store_out_main(const float (&s)[76], const float (&l)[N], uint32_t a0, uint32_t (&t)[6]) {
    float z = 0.f;
#pragma unroll
    for (int j = 0; j < 16; j += 2) {
        const float* v = &s[4 * j];
        const float* r = &l[2 * j];
        const uint32_t r0 = pack2(fmaf(v[0], r[0], z), fmaf(v[1], r[1], z)), r1 = pack2(fmaf(v[2], r[0], z), fmaf(v[3], r[1], z));
        const uint32_t r2 = pack2(fmaf(v[4], r[2], z), fmaf(v[5], r[3], z)), r3 = pack2(fmaf(v[6], r[2], z), fmaf(v[7], r[3], z));
        stsm4t(a0 + j * 1024, r0, r1, r2, r3);
        z = __uint_as_float((r0 & r1 & r2) & r3 & blockIdx.y);
    }
#pragma unroll
    for (int k = 0; k < 6; k++) t[k] = pack2(fmaf(s[64 + 2 * k], l[32 + (k >> 1) * 2], z), fmaf(s[65 + 2 * k], l[33 + (k >> 1) * 2], z));
}
__device__ __forceinline__ void store_out_tail(const uint32_t (&t)[6], uint32_t a1) {
    stsm4t(a1, t[0], t[1], t[2], t[3]);
    stsm2t(a1 + 2048, t[4], t[5]);
}

__device__ __forceinline__ uint32_t softmax_fast(float (&s)[76], float (&l)[38], uint32_t paddr, uint32_t nbar, uint32_t nphase, bool wait_pv0) {
    uint32_t ok = 0;
#pragma unroll
    for (int g = 0; g < 10; g++) {
        uint32_t r[4];
#pragma unroll
        for (int h = 0; h < 2; h++) {
            if (8 * g + 4 * h < 76) {
                float* v = &s[8 * g + 4 * h];
                ex2v(v[0]); ex2v(v[1]); ex2v(v[2]); ex2v(v[3]);
                r[2 * h] = pack2v(v[0], v[1]);
                r[2 * h + 1] = pack2v(v[2], v[3]);
                addv(v[2], v[0]); addv(v[3], v[1]);
                addv(l[4 * g + 2 * h], v[2]); addv(l[4 * g + 2 * h + 1], v[3]);
            }
        }
        if (g == 0) bar_sync_if<BAR_F, 384>(wait_pv0);
        if (g < 9) stsm4t(paddr + g * 2048, r[0], r[1], r[2], r[3]);
        else stsm2t(paddr + g * 2048, r[0], r[1]);
        if (g == 7) ok = mbar_test(nbar, nphase);
    }
    return ok;
}
__device__ __forceinline__ void softmax_nosum(float (&s)[76], uint32_t paddr) {
#pragma unroll
    for (int g = 0; g < 10; g++) {
        uint32_t r[4];
#pragma unroll
        for (int h = 0; h < 4; h++) {
            if (8 * g + 2 * h < 76) {
                ex2v(s[8 * g + 2 * h]); ex2v(s[8 * g + 2 * h + 1]);
                r[h] = pack2v(s[8 * g + 2 * h], s[8 * g + 2 * h + 1]);
            }
        }
        if (g < 9) stsm4t(paddr + g * 2048, r[0], r[1], r[2], r[3]);
        else stsm2t(paddr + g * 2048, r[0], r[1]);
    }
}
__device__ __forceinline__ void add_tile_sums(float (&l)[38], uint32_t paddr) {
#pragma unroll
    for (int g = 0; g < 10; g++) {
        uint32_t r[4];
        if (g >= CHAIN_D) paddr += __float_as_uint(l[4 * (g - CHAIN_D) + 3]) & blockIdx.y;
        if (g < 9) asm volatile("ldmatrix.sync.aligned.m8n8.x4.trans.shared.b16 {%0,%1,%2,%3}, [%4];" : "=r"(r[0]), "=r"(r[1]), "=r"(r[2]), "=r"(r[3]) : "r"(paddr + g * 2048) : "memory");
        else asm volatile("ldmatrix.sync.aligned.m8n8.x2.trans.shared.b16 {%0,%1}, [%2];" : "=r"(r[0]), "=r"(r[1]) : "r"(paddr + g * 2048) : "memory");
#pragma unroll
        for (int h = 0; h < 4; h++) {
            if (8 * g + 2 * h < 76) {
                addv(l[4 * g + (h >> 1) * 2], __uint_as_float(r[h] << 16));
                addv(l[4 * g + (h >> 1) * 2 + 1], __uint_as_float(r[h] & 0xFFFF0000u));
            }
        }
    }
}
__device__ __forceinline__ void softmax_safe(const float (&s)[76], float (&l)[38], uint32_t paddr, uint32_t maddr) {
#pragma unroll
    for (int j = 0; j < 19; j += 2) {
        uint32_t r[4];
#pragma unroll
        for (int jj = 0; jj < 2; jj++) {
            if (j + jj < 19) {
                const float* v = &s[4 * (j + jj)];
                float m0, m1;
                asm volatile("ld.shared.v2.f32 {%0,%1}, [%2];" : "=f"(m0), "=f"(m1) : "r"(maddr + (j + jj) * 32) : "memory");
                const float p0 = ex2(v[0] - m0), p1 = ex2(v[1] - m1), p2 = ex2(v[2] - m0), p3 = ex2(v[3] - m1);
                l[2 * (j + jj)] += p0; l[2 * (j + jj) + 1] += p1;
                l[2 * (j + jj)] += p2; l[2 * (j + jj) + 1] += p3;
                r[2 * jj] = pack2(p0, p1); r[2 * jj + 1] = pack2(p2, p3);
            }
        }
        if (j + 1 < 19) stsm4t(paddr + j * 1024, r[0], r[1], r[2], r[3]);
        else stsm2t(paddr + j * 1024, r[0], r[1]);
    }
}

__device__ __forceinline__ uint32_t stsm_lane_off(int tid) {
    const int lane = tid & 31, w = (tid >> 5) & 3, mi = lane >> 3, r = lane & 7;
    return ((mi >> 1) * 8 + r) * 128 + (((2 * w + (mi & 1)) ^ r) << 4);
}

template <int TA, int C>
__device__ __forceinline__ void issue_quarter(float (&s)[76], uint32_t a16) {
    if (C == 0) wg_fence();
#pragma unroll
    for (int k = 0; k < 4; k++) mma152<TA, TA ? 64 : 256>(s, a16 + (TA ? C * 512 + k * 128 : C * 64 + k * 2), S16 + C * (CH >> 4) + k * 2, C + k > 0);
}
template <int TA>
__device__ __forceinline__ void issue_s_op(float (&s)[76], uint32_t a16) {
    issue_quarter<TA, 0>(s, a16); issue_quarter<TA, 1>(s, a16); issue_quarter<TA, 2>(s, a16); issue_quarter<TA, 3>(s, a16);
    wg_commit();
}
template <int TA>
__device__ __forceinline__ void issue_rest_chasing(float (&s)[76], uint32_t a16, bool chase) {
    bar_sync_if<BAR_C + 2, 256>(chase);
    if (TA) wg_fence();
    issue_quarter<TA, 2>(s, a16);
    bar_sync_if<BAR_C + 1, 256>(chase);
    issue_quarter<TA, 1>(s, a16);
    bar_sync_if<BAR_C + 3, 256>(chase);
    issue_quarter<TA, 3>(s, a16);
    wg_commit();
}
__device__ __forceinline__ uint32_t slot16(uint32_t sl) { return S16 + ((OFF_RING + sl * TILE) >> 4); }

__device__ __forceinline__ uint32_t s_round(const uint32_t sbase, const int tid, Ring& ring, const int nu, const bool safe, const bool emit_in,
                                            const uint32_t rel0, const uint32_t rank) {
    const int lane = tid & 31;
    const uint32_t lane_off = stsm_lane_off(tid);
    float s[76], l[38];
    uint32_t bad = 0;
    ring.adv(1);
#pragma unroll 1
    for (int u = 0; u < nu; u++) {
        const bool paired = u + 1 < nu;
        uint32_t t1 = 0, t2 = 0, t3 = 0;
#pragma unroll 1
        for (int pass = safe ? 0 : 1; pass < 2; pass++) {
            const float init = pass == 0 ? -INFINITY : 0.f;
#pragma unroll
            for (int i = 0; i < 38; i++) l[i] = init;
            uint32_t sl = ring.slot();
            {
                const bool first = pass == 0 || !safe;
                bar_sync_if<BAR_C, 384>(first && u == 0);
                mbar_wait(sbase + OFF_FULL + sl * 8, ring.phase());
                bar_sync_if<BAR_C, 384>(first && u > 0);
                issue_quarter<0, 0>(s, slot16(sl));
                issue_rest_chasing<0>(s, slot16(sl), first);
                bar_arrive_if<BAR_G + 1, 256>(!safe);
                PROF(0, u * 128 + 2);
                GT(1 + u * 4);
            }
#pragma unroll 1
            for (int j = 0;; j += (j == 0 && !safe) ? 2 : 1) {
                const bool j2 = j == 2 && !safe;
                ring.adv((safe && (j == 0 || pass == 0)) ? 1 : ((j == 15 || j2) ? 3 : 2));
                const uint32_t rel = rel0 + sl * 8;
                sl = ring.slot();
                const uint32_t nbar = sbase + OFF_FULL + sl * 8, nphase = ring.phase(), na16 = slot16(sl);
                const uint32_t pa = sbase + (4 + (j & 1)) * CH + lane_off;
                wg_wait0();
                reg_fence(s);
                PROF2(0, u * 128 + j * 4 + 3);
                release_slot(rel, lane, 2);
                if (j2) {
                    bar_arrive<BAR_A, 384>();
                    bar_sync<BAR_D, 256>();
                    add_tile_sums(l, pa + CH);
                }
                uint32_t ready = 0;
                if (!safe) ready = softmax_fast(s, l, pa, nbar, nphase, j2);
                else if (pass == 1) softmax_safe(s, l, pa, sbase + OFF_RL + (tid_now() & 3) * 8);
                else {
#pragma unroll
                    for (int c = 0; c < 19; c++) {
                        l[2 * c] = fmaxf(l[2 * c], fmaxf(s[4 * c], s[4 * c + 2]));
                        l[2 * c + 1] = fmaxf(l[2 * c + 1], fmaxf(s[4 * c + 1], s[4 * c + 3]));
                    }
                }
                if (j == 15) break;
                PROF2(0, u * 128 + j * 4 + 4);
                if (!ready) mbar_wait(nbar, nphase);
                issue_s_op<0>(s, na16);
                fence_async_smem();
                bar_sync_if<BAR_A, 384>(pass == 1);
                PROF(0, u * 128 + j * 4 + 6);
            }
            TS(t1);
            fence_async_smem();
            bar_sync_if<BAR_A, 384>(pass == 1);
            TS(t2);
            if (pass == 0) {
                column_reduce1<true>(l, sbase);
                bar_sync<BAR_E, 128>();
                const float2 m = column_reduce2<true>(sbase);
                const int t = tid_now();
                if (t < 76) asm volatile("st.shared.v2.f32 [%0], {%1,%2};" ::"r"(sbase + OFF_RL + t * 8), "f"(m.x), "f"(m.y) : "memory");
                bar_sync<BAR_E, 128>();
            }
        }
#pragma unroll
        for (int i = 0; i < 38; i++) asm volatile("" : "+f"(l[i])::"memory");
        {
            const int tn = tid_now();
            const uint32_t la = sbase + 3 * CH + (tn & 31) * 128 + (((tn >> 5) ^ (tn & 7)) << 4);
#pragma unroll
            for (int j = 0; j < 16; j += 4)
                stsm4t(la + j * 1024, pack2(l[2 * j], l[2 * j + 1]), pack2(l[2 * j + 2], l[2 * j + 3]), pack2(l[2 * j + 4], l[2 * j + 5]), pack2(l[2 * j + 6], l[2 * j + 7]));
            stsm4t(la + 15 * 1024, pack2(l[30], l[31]), pack2(l[32], l[33]), pack2(l[34], l[35]), pack2(l[36], l[37]));
            fence_async_smem();
            bar_sync<BAR_E, 128>();
            wg_fence();
#pragma unroll
            for (int k = 0; k < (LSPLIT ? 4 : 2); k++) mma152_ones(s, S16 + 3 * (CH >> 4) + k * 2, k > 0);
            wg_commit();
            bar_arrive<BAR_G + 1, 256>();
            wg_wait0();
            reg_fence(s);
#pragma unroll
            for (int c = 0; c < 19; c++) {
                asm volatile("rcp.approx.ftz.f32 %0, %1;" : "=f"(l[2 * c]) : "f"(s[4 * c]));
                asm volatile("rcp.approx.ftz.f32 %0, %1;" : "=f"(l[2 * c + 1]) : "f"(s[4 * c + 1]));
            }
        }
        uint32_t tail[6] = {0, 0, 0, 0, 0, 0};
#pragma unroll 1
        for (int i = 0; i < 7; i += paired ? 1 : 2) {
            const uint32_t sl = ring.slot();
            PROF2(0, u * 128 + 64 + i * 4);
            mbar_wait(sbase + OFF_FULL + sl * 8, ring.phase());
            bar_sync_if<BAR_D, 256>(i > 0);
            bar_sync_if<BAR_C, 384>(i == 0);
            PROF2(0, u * 128 + 64 + i * 4 + 1);
            issue_quarter<1, 0>(s, slot16(sl));
            if (i == 0) {
                uint32_t acc = 0;
#pragma unroll
                for (int c = 0; c < 38; c++) {
                    asm volatile("" : "+f"(l[c]));
                    acc = max(acc, __float_as_uint(l[c]) - (90u << 23));
                }
                const uint32_t any = __any_sync(0xffffffffu, (acc >> 29) != 0) ? 1u : 0u;
                const bool emit = safe ? emit_in : any == 0;
                bad |= any << u;
                asm volatile("st.shared.u32 [%0], %1;" ::"r"(sbase + OFF_EMIT), "r"((uint32_t)emit) : "memory");
            }
            if (i == 0 && !paired) {
                const int tn = tid_now();
#pragma unroll
                for (int c = 0; c < 19; c++)
                    if (tn < 4) asm volatile("st.shared.v2.f32 [%0], {%1,%2};" ::"r"(sbase + OFF_RL + tn * 8 + c * 32), "f"(l[2 * c]), "f"(l[2 * c + 1]) : "memory");
                asm volatile("{\n.reg .pred p;\nsetp.lt.s32 p, %3, 2;\n@p st.async.weak.shared::cluster.mbarrier::complete_tx::bytes.u32 [%0], %1, [%2];\n}" ::"r"(
                                 rel0 - OFF_EMPTY + OFF_FLAG + rank * 4), "r"(bad), "r"(rel0 - OFF_EMPTY + OFF_FBAR), "r"(safe ? 2 : tn) : "memory");
            }
            issue_rest_chasing<1>(s, slot16(sl), i == 0);
            bar_sync_if<BAR_A, 384>(paired);
            bar_arrive_if<BAR_G, 256>(!paired && i < 6);
            PROF(0, u * 128 + 64 + i * 4 + 2);
            ring.adv(paired || i < 6 ? 2 : 1);
            if (paired && i > 0) {
                store_out_tail(tail, sbase + (5 - (i & 1)) * CH + 16384 + lane_off);
                fence_async_smem();
                bar_arrive<BAR_T, 160>();
            }
            bar_sync_if<BAR_K, 160>(i > 0);
            wg_wait0();
            reg_fence(s);
            PROF(0, u * 128 + 64 + i * 4 + 3);
            bar_arrive_if<BAR_G, 256>(paired && i == 6);
            release_slot(rel0 + sl * 8, lane, 2);
            if (blockIdx.z == 0)
                store_out_main(s, l, sbase + (paired ? OFF_STG : 4 * CH) + lane_off, tail);
            if (!paired || i == 6) store_out_tail(tail, sbase + (paired ? 5 * CH : 4 * CH + 16384) + lane_off);
            fence_async_smem();
            bar_arrive<BAR_H, 160>();
        }
    }
    return bad;
}

struct Producer {
    Ring ring;
    int pu, pp;
    const CUtensorMap* map;
    int c0, c1, c3;
    uint32_t xdst, bytes;
    uint64_t pol;
};
constexpr uint64_t POL_FIRST = 0x12F0000000000000ull, POL_NORMAL = 0x1000000000000000ull;

__device__ __forceinline__ void next_tile(const CUtensorMap* maps, Producer& pr, const uint32_t sbase, const int nu, const bool safe, const int bh0) {
    int q = pr.pp + 1;
    q = (q == -16 && !safe) ? 0 : q;
    q += (q > 32 && pr.pu + 1 == nu) ? 1 : 0;
    const bool wrap = q >= 46;
    q = wrap ? 0 : q;
    pr.pu += wrap ? 1 : 0;
    pr.pp = q;
    q ^= ((q >> 1) == 1 && !safe) ? 1 : 0;
    const int bh = bh0 + 4 * pr.pu;
    const bool proj = q >= 32, pro = q < -16;
    const int isk = q < 0 ? 1 : (0x2AAAAAABu >> (q & 31)) & 1;
    const bool wq = pro || (proj && (q & 1)), wo = proj && !(q & 1);
    const int n = q < 0 ? (pro ? q + 23 : q + 16) : (proj ? (q - 32) >> 1 : (q + 2 * isk - 1) >> 1);
    pr.map = maps + (wq ? 3 : (wo ? 4 : 2 - isk));
    pr.c0 = wo ? n * 64 : 0;
    pr.c1 = wo ? 0 : n * 64;
    pr.c3 = (wq || wo) ? (bh + (proj && wq ? 4 : 0)) & 15 : bh;
    pr.bytes = wq ? TILE + CH : TILE;
    pr.xdst = (wq && q < 36) ? sbase + (pro ? (0x4503210 >> (4 * n)) & 7 : 4 + (n & 1)) * CH : 0;
    pr.pol = (wq || wo) ? POL_NORMAL : POL_FIRST;
}

__device__ __forceinline__ void tma_load_2d(uint32_t dst, const void* m, uint32_t bar, int c0, int c1) {
    asm volatile("cp.async.bulk.tensor.2d.shared::cluster.global.mbarrier::complete_tx::bytes [%0], [%1, {%3, %4}], [%2];" ::"r"(dst), "l"(m), "r"(bar),
                 "r"(c0), "r"(c1) : "memory");
}
__device__ __forceinline__ void tma_add_2d(const CUtensorMap* m, int c0, int c1, uint32_t src) {
    asm volatile("cp.reduce.async.bulk.tensor.2d.global.shared::cta.add.tile.bulk_group [%0, {%1, %2}], [%3];" ::"l"(m), "r"(c0), "r"(c1), "r"(src) : "memory");
    asm volatile("cp.async.bulk.commit_group;" ::: "memory");
}

__device__ __forceinline__ void load_tile(const CUtensorMap* maps, Producer& pr, const uint32_t sbase, const int nu, const int row0, const uint32_t rank) {
    if (pr.pu >= nu) return;
    const uint32_t sl = pr.ring.slot();
    const uint32_t full = sbase + OFF_FULL + sl * 8;
    const uint32_t dst = sbase + OFF_RING + sl * TILE + rank * 16384;
    mbar_wait(full + (OFF_EMPTY - OFF_FULL), pr.ring.phase() ^ 1);
    if (elect_one()) {
        asm volatile("mbarrier.arrive.expect_tx.shared::cta.b64 _, [%0], %1;" ::"r"(full), "r"(pr.bytes) : "memory");
        asm volatile(
            "cp.async.bulk.tensor.5d.shared::cluster.global.mbarrier::complete_tx::bytes.multicast::cluster.L2::cache_hint [%0], [%1, {%3, %5, %5, %4, %6}], [%2], %7, %8;" ::"r"(dst),
            "l"(pr.map), "r"(full), "r"(pr.c0), "r"((pr.c1 >> 3) + 4 * rank), "r"(0), "r"(pr.c3), "h"((uint16_t)3), "l"(pr.pol) : "memory");
        if (pr.xdst) tma_load_2d(pr.xdst, maps, full, pr.c1, row0);
    }
    pr.ring.adv(1);
}
#define NEXT() next_tile(maps, pr, sbase, nu, safe, bh0)
#define LOAD() load_tile(maps, pr, sbase, nu, row0, rank)

__device__ __forceinline__ void emit_tile(const Params& p, const uint32_t sbase, const int i, const uint32_t a0, const uint32_t a1, const int br,
                                          const int row0) {
    uint32_t emit;
    asm volatile("ld.shared.u32 %0, [%1];" : "=r"(emit) : "r"(sbase + OFF_EMIT) : "memory");
    if (elect_one() && emit) {
        if (a1) tma_add_2d(&p.maps[11], br * 448 + i * 64, row0 + 128, a1);
        if (a0) tma_add_2d(&p.maps[10], br * 448 + i * 64, row0, a0);
    }
    __syncwarp();
}

template <int OID>
__device__ __forceinline__ void o_round(const Params& p, const uint32_t sbase, const int tid, const int warp, Ring& ring, Producer& pr, const int nu,
                                        const bool safe, const uint32_t rel0, const int br, const int bh0, const int row0, const uint32_t rank) {
    const int lane = tid & 31;
    const bool lead = (warp & 3) == 1;
    const CUtensorMap* maps = &p.maps[br * 5];
    float o0[76], o1[76];
    if (OID == 0 && lead) {
        pr.pu = 0; pr.pp = safe ? -24 : -21;
        if (safe) {
#pragma unroll 1
            for (int i = 0; i < 3; i++) { NEXT(); LOAD(); }
        }
    }
#pragma unroll 1
    for (int ph = 0; ph < 2 * nu; ph++) {
        const bool isq = (ph & 1) == 0, pro = ph == 0;
        const int nops = isq ? 7 : 16;
        if (OID == 1) {
            if (!isq && !safe) {
                Ring kr = ring; kr.adv(4);
                const uint32_t ksl = kr.slot(), k16 = slot16(ksl);
                mbar_wait(sbase + OFF_FULL + ksl * 8, kr.phase());
                bar_sync_if_after<BAR_G + 1, 256>(true, k16, k16);
                issue_s_op<0>(o0, k16);
                bar_arrive<BAR_A, 384>();
                if (ph > 1) {
                    if (lead) {
                        bar_sync<BAR_H, 160>();
                        emit_tile(p, sbase, 6, sbase + OFF_STG, sbase + 5 * CH, br, row0);
                        asm volatile("cp.async.bulk.wait_group.read 1;" ::: "memory");
                        __syncwarp();
                    }
                    bar_sync<BAR_K, 128>();
                }
                const uint32_t pa = sbase + 5 * CH + stsm_lane_off(tid_now());
                wg_wait0();
                reg_fence(o0);
                release_slot(rel0 + ksl * 8, lane, 2);
                softmax_nosum(o0, pa);
                fence_async_smem();
                bar_arrive<BAR_D, 256>();
            } else {
                asm volatile("cp.async.bulk.wait_group.read 0;" ::: "memory");
                __syncwarp();
                bar_arrive_if<BAR_A, 384>(!pro);
            }
            if (ph == 2 && lead) {
                asm volatile(
                    "{\n.reg .pred p;\n.reg .u32 c, v, t;\nmov.u32 c, 0;\n"
                    "ld.shared.u32 t, [%1];\n"
                    "Z_LOOP:\n"
                    "ld.acquire.gpu.global.u32 v, [%0];\n"
                    "sub.u32 v, v, t;\n"
                    "setp.ge.s32 p, v, 0;\n"
                    "vote.sync.all.pred p, p, 0xffffffff;\n"
                    "@p bra.uni Z_DONE;\n"
                    "add.u32 c, c, 1;\n"
                    "setp.lt.u32 p, c, 0x1000000;\n"
                    "@p bra.uni Z_LOOP;\n"
                    "trap;\n"
                    "Z_DONE:\n}" ::"l"(&g_zero_cnt), "r"(sbase + OFF_ZT) : "memory");
            }
        } else if (!pro && lead) {
            const int n = isq ? 1 : (safe ? 18 : 3);
#pragma unroll 1
            for (int i = 0; i < n; i++) { NEXT(); LOAD(); }
        }
#pragma unroll 1
        for (int i = 0; i < nops; i++) {
            const uint32_t sl = ring.slot();
            const uint32_t a16 = slot16(sl) + OID * 128;
            const uint32_t bi = pro ? (0x4503210 >> (4 * i)) & 7 : 4 + (i & 1);
            const uint32_t b16 = S16 + bi * (CH >> 4);
            const bool last = i + 1 == nops;
            const bool oo = i == 14 || (i == 0 && !isq && !safe);
            PROF2(1 + OID, ph * 64 + i * 4);
            const uint32_t fphase = ring.phase();
            uint32_t n = 2;
            if (pro || oo) n = 1;
            if (last) n = isq ? (safe ? 1 : 4) : 2;
            ring.adv(n);
            if (OID == 0) {
                bar_sync_if<BAR_A, 384>(!pro && i != 15 && !(isq && i == 0));
                bar_sync_if<BAR_F, 256>(pro && i > 0);
                bar_arrive_if<BAR_F, 384>(i == 1 && !isq && !safe);
            } else {
                bar_sync_if<BAR_B, 256>(safe);
            }
            PROF2(1 + OID, ph * 64 + i * 4 + 1);
            mbar_wait(sbase + OFF_FULL + sl * 8, fphase);
            if (OID == 0) bar_sync_if_after<BAR_A, 384>(i == 15 || (isq && i == 0 && !pro), a16, b16);
            else {
                bar_sync_if<BAR_G + 1, 256>(i == 15);
                bar_sync_if_after<BAR_B, 256>(!safe, a16, b16);
            }
            uint32_t ta = 0, tb = 0, tc = 0, td = 0, te = 0, tf = 0; TS(ta);
            wg_fence();
#pragma unroll
            for (int k = 0; k < 4; k++) mma152<1, 256>(o0, a16 + k * 512, b16 + k * 2, k > 0 || i > 0);
            wg_commit();
#pragma unroll
            for (int k = 0; k < 4; k++) mma152<1, 256>(o1, a16 + 64 + k * 512, b16 + k * 2, k > 0 || i > 0);
            wg_commit();
            if (OID == 0) {
                bar_arrive<BAR_B, 256>();
                if (lead && !(pro && i == 0) && !last) { NEXT(); LOAD(); }
            } else {
                bar_arrive_if<BAR_F, 256>(pro && !last);
                bar_arrive_if<BAR_D, 256>(isq && !pro && !last);
                bar_arrive_if<BAR_A, 384>(oo);
                if (last && (warp & 3) == 2) {
                    int phv;
                    asm volatile("mov.u32 %0, %1;" : "=r"(phv) : "r"(ph));
                    const bool k1 = (phv & 1) == 0, wq0 = !k1 && phv + 1 < 2 * nu;
                    const int bh = bh0 + 4 * (phv >> 1);
                    Producer pr;
                    pr.pu = 0;
                    pr.ring.t6 = sl + 3 * fphase; pr.ring.adv(2);
                    pr.map = maps + (k1 ? 1 : (wq0 ? 3 : 4));
                    pr.c0 = (k1 || wq0) ? 0 : 64;
                    pr.c1 = k1 ? 64 : 0;
                    pr.c3 = k1 ? bh : (bh + (wq0 ? 4 : 0)) & 15;
                    pr.bytes = wq0 ? TILE + CH : TILE;
                    pr.xdst = wq0 ? sbase + 4 * CH : 0;
                    pr.pol = k1 ? POL_FIRST : POL_NORMAL;
                    LOAD();
                }
                if (lead && isq && !pro && !last) {
                    if (i > 0) {
                        asm volatile("cp.async.bulk.wait_group.read 0;" ::: "memory");
                        if (elect_one()) tma_load_2d(sbase + (5 - (i & 1)) * CH, maps, sbase + OFF_FULL + ring.slot() * 8, (i + 1) * 64, row0);
                        __syncwarp();
                    }
                    bar_sync<BAR_H, 160>();
                    emit_tile(p, sbase, i, sbase + OFF_STG, 0, br, row0);
                }
            }
            PROF2(1 + OID, ph * 64 + i * 4 + 2);
            TS(tb);
            if (last) {
                const uint32_t qa = sbase + OID * 2 * CH + stsm_lane_off(tid_now());
                const float c = 0.0625f * 1.4426950408889634f;
                if (OID == 0) {
                    bar_sync_if<BAR_G, 256>(isq && !pro);
                    wg_wait1();
                } else {
                    bar_sync<BAR_C, 384>();
                    wg_wait1();
                }
                reg_fence(o0);
                TS(tc);
                if (isq) store_tile_t<true>(o0, qa, c); else store_tile_t<false>(o0, qa, c);
                fence_async_smem();
                bar_arrive<BAR_C + 2 * OID, OID == 0 ? 384 : 256>();
                TS(td);
                wg_wait0();
                reg_fence(o1);
                TS(te);
                release_slot(rel0 + sl * 8, lane, 1);
                if (isq) store_tile_t<true>(o1, qa + CH, c); else store_tile_t<false>(o1, qa + CH, c);
                fence_async_smem();
                bar_arrive<BAR_C + 2 * OID + 1, 256>();
                PROF2(1 + OID, ph * 64 + i * 4 + 3);
                if (OID == 0) { pr.pp += (!isq && ph + 1 == 2 * nu) ? 2 : 1; pr.ring.adv(1); }
            } else {
                wg_wait0();
                reg_fence(o0);
                reg_fence(o1);
                PROF2(1 + OID, ph * 64 + i * 4 + 3);
                release_slot(rel0 + sl * 8, lane, 1);
                if (OID == 0) {
                    if (lead && !pro && !oo) { NEXT(); LOAD(); }
                } else {
                    bar_arrive_if<BAR_A, 384>(!pro && !oo);
                    bar_arrive_if<BAR_F, 384>(oo && i == 0);
                }
            }
            if (OID == 1 && lead && isq && !pro && !last) {
                asm volatile("cp.async.bulk.wait_group.read 0;" ::: "memory");
                __syncwarp();
                bar_arrive<BAR_K, 160>();
                bar_sync<BAR_T, 160>();
                emit_tile(p, sbase, i, 0, sbase + (4 + (i & 1)) * CH + 16384, br, row0);
            }
        }
    }
    if (OID == 0) {
        if (lead) { NEXT(); LOAD(); }
#pragma unroll 1
        for (int i = 1; i < 7; i += 2) {
            const uint32_t sl = ring.slot();
            bar_sync<BAR_G, 256>();
            mbar_wait(sbase + OFF_FULL + sl * 8, ring.phase());
            issue_s_op<1>(o0, slot16(sl));
            bar_arrive<BAR_D, 256>();
            if (lead) { NEXT(); LOAD(); NEXT(); }
            ring.adv(2);
            if (i == 1) load_rl(o1, sbase);
            bar_sync_if<BAR_K + 1, 160>(i > 1);
            wg_wait0();
            reg_fence(o0);
            release_slot(rel0 + sl * 8, lane, 2);
            if (lead) LOAD();
            const uint32_t a = sbase + 5 * CH + stsm_lane_off(tid_now());
            uint32_t tail[6];
            store_out_main(o0, o1, a, tail);
            store_out_tail(tail, a + 16384);
            fence_async_smem();
            bar_arrive<BAR_H + 1, 160>();
        }
    } else if (lead || (warp & 3) == 2) {
        const int odd = lead ? 0 : 1;
        const uint32_t a = sbase + (4 + odd) * CH;
#pragma unroll 1
        for (int i = odd; i < 7; i += 2) {
            bar_sync_if<BAR_H, 160>(!odd);
            bar_sync_if<BAR_H + 1, 160>(odd);
            emit_tile(p, sbase, i, a, a + 16384, br, row0);
            PROF(2, 700 + i * 2);
            asm volatile("cp.async.bulk.wait_group.read 0;" ::: "memory");
            __syncwarp();
            PROF(2, 701 + i * 2);
            bar_arrive_if<BAR_K, 160>(!odd && i < 5);
            bar_arrive_if<BAR_K + 1, 160>(odd && i < 5);
        }
    }
}

__device__ __forceinline__ uint32_t read_redo(uint32_t sbase) {
    uint32_t a, b;
    mbar_wait(sbase + OFF_FBAR, 0);
    asm volatile("ld.shared.v2.u32 {%0,%1}, [%2];" : "=r"(a), "=r"(b) : "r"(sbase + OFF_FLAG) : "memory");
    return __shfl_sync(0xffffffffu, a | b, 0);
}

template <int OID>
__device__ __forceinline__ void o_role(const Params& p, const uint32_t sbase, const int tid, const int warp, const uint32_t rel0, const int br,
                                       const int bh_first, const int row0, const uint32_t rank) {
    Ring ring; ring.t6 = 0;
    Producer pr; pr.ring.t6 = 3;
    uint32_t redo = 0;
#pragma unroll 1
    for (int r = -1; r < 4; r++) {
        if (r < 0 || ((redo >> r) & 1)) {
            o_round<OID>(p, sbase, tid, warp, ring, pr, r < 0 ? 4 : 1, r >= 0, rel0, br, r < 0 ? bh_first : bh_first + 4 * r, row0, rank);
            if (r < 0) redo = read_redo(sbase);
            cluster_sync_relaxed();
            if (redo == 0) break;
        }
    }
}

__global__ void __cluster_dims__(2, 1, 1) __launch_bounds__(384, 1) fused_mha_kernel(const __grid_constant__ Params p) {
    extern __shared__ __align__(1024) uint8_t smem_raw[];
    const uint32_t sbase = (uint32_t)__cvta_generic_to_shared(smem_raw);
    const int warp = __shfl_sync(0xffffffffu, threadIdx.x >> 5, 0);
    const int tid = threadIdx.x & 127;
    const uint32_t rank = blockIdx.x & 1;
    const int cl = (int)(blockIdx.x >> 1) - 2;
    if (cl < 0) {
        uint4* z = reinterpret_cast<uint4*>(p.out) + blockIdx.x * 68096;
#pragma unroll 1
        for (int i = threadIdx.x; i < 68096; i += 384) z[i] = make_uint4(0, 0, 0, 0);
        asm volatile("fence.proxy.async;" ::: "memory");
        __threadfence();
        __syncthreads();
        if (threadIdx.x == 0) atomicAdd(&g_zero_cnt, 1u);
        return;
    }
    const int bb = cl >> 2;
    const int br = bb >> 3;
    const int bh_first = (bb & 7) * 16 + (cl & 3);
    const int row0 = (bb & 7) * 304 + rank * NQ;
    if (warp == 0) {
        if (elect_one()) {
#pragma unroll
            for (int i = 0; i < 3; i++) {
                asm volatile("mbarrier.init.shared::cta.b64 [%0], 1;" ::"r"(sbase + OFF_FULL + i * 8) : "memory");
                asm volatile("mbarrier.init.shared::cta.b64 [%0], 16;" ::"r"(sbase + OFF_EMPTY + i * 8) : "memory");
            }
            asm volatile("mbarrier.init.shared::cta.b64 [%0], 1;" ::"r"(sbase + OFF_FBAR) : "memory");
            asm volatile("mbarrier.arrive.expect_tx.shared::cta.b64 _, [%0], 8;" ::"r"(sbase + OFF_FBAR) : "memory");
            asm volatile("fence.mbarrier_init.release.cluster;" ::: "memory");
            fence_async_smem();
#pragma unroll
            for (int i = 0; i < 3; i++) {
                const uint32_t full = sbase + OFF_FULL + i * 8;
                asm volatile("mbarrier.arrive.expect_tx.shared::cta.b64 _, [%0], %1;" ::"r"(full), "r"(TILE + CH) : "memory");
#pragma unroll
                for (int h = 0; h < 2; h++)
                    asm volatile("cp.async.bulk.tensor.5d.shared::cluster.global.mbarrier::complete_tx::bytes [%0], [%1, {%3, %3, %3, %4, %5}], [%2];" ::"r"(
                                     sbase + OFF_RING + i * TILE + h * 16384),
                                 "l"(&p.maps[br * 5 + 3]), "r"(full), "r"(0), "r"(i * 8 + 4 * h), "r"(cl & 3) : "memory");
                tma_load_2d(sbase + i * CH, &p.maps[br * 5], full, i * 64, row0);
            }
        }
    }
    asm volatile("{\n.reg .pred p;\nsetp.ne.u32 p, %0, 1024;\n@p trap;\n}" ::"r"(sbase & 0x3FFFF));
    uint32_t rel0;
    asm volatile("mapa.shared::cluster.u32 %0, %1, %2;" : "=r"(rel0) : "r"(sbase + OFF_EMPTY), "r"(threadIdx.x & 1));
    cluster_sync_relaxed();

    if (warp < 4) {
        asm volatile("setmaxnreg.dec.sync.aligned.u32 136;");
        if (warp == 0) {
            if (elect_one()) {
                const uint32_t e = g_epoch[blockIdx.x - 4] + 1;
                g_epoch[blockIdx.x - 4] = e;
                asm volatile("st.shared.u32 [%0], %1;" ::"r"(sbase + OFF_ZT), "r"(4 * e) : "memory");
            }
            __syncwarp();
        }
        Ring ring; ring.t6 = 0;
        uint32_t redo = 0, bad = 0;
#pragma unroll 1
        for (int r = -1; r < 4; r++) {
            if (r < 0 || ((redo >> r) & 1)) {
                const uint32_t b = s_round(sbase, tid, ring, r < 0 ? 4 : 1, r >= 0, r >= 0 && ((bad >> r) & 1), rel0, rank);
                if (r < 0) { bad = b; redo = read_redo(sbase); }
                cluster_sync_relaxed();
                if (redo == 0) break;
            }
        }
    } else {
        asm volatile("setmaxnreg.inc.sync.aligned.u32 184;");
        if (warp < 8) o_role<0>(p, sbase, tid, warp, rel0, br, bh_first, row0, rank);
        else o_role<1>(p, sbase, tid, warp, rel0, br, bh_first, row0, rank);
    }
}

typedef CUresult (*EncodeFn)(CUtensorMap*, CUtensorMapDataType, cuuint32_t, void*, const cuuint64_t*, const cuuint64_t*, const cuuint32_t*,
                             const cuuint32_t*, CUtensorMapInterleave, CUtensorMapSwizzle, CUtensorMapL2promotion, CUtensorMapFloatOOBfill);

void encode(EncodeFn fn, CUtensorMap* m, void* ptr, int rank, uint64_t d0, uint64_t d1, uint64_t d3, uint64_t d4, uint64_t s1, uint64_t s2,
            uint64_t s3, uint64_t s4, uint32_t b1) {
    cuuint64_t dims[5] = {d0, d1, 4, d3, d4};
    cuuint64_t strides[4] = {s1, s2, s3, s4};
    cuuint32_t box[5] = {64, b1, 4, 4, 1};
    cuuint32_t es[5] = {1, 1, 1, 1, 1};
    fn(m, CU_TENSOR_MAP_DATA_TYPE_BFLOAT16, rank, ptr, dims, strides, box, es, CU_TENSOR_MAP_INTERLEAVE_NONE, CU_TENSOR_MAP_SWIZZLE_128B,
       PROMO, CU_TENSOR_MAP_FLOAT_OOB_FILL_NONE);
}

}

extern "C" void kernel_launch(void* const* d_in, const int* in_sizes, int n_in, void* d_out, int out_size) {
    (void)in_sizes; (void)n_in; (void)out_size;
    static EncodeFn fn = nullptr;
    if (!fn) {
        void* f = nullptr;
        cudaDriverEntryPointQueryResult q;
        cudaGetDriverEntryPoint("cuTensorMapEncodeTiled", &f, cudaEnableDefault, &q);
        fn = (EncodeFn)f;
        cudaFuncSetAttribute(fused_mha_kernel, cudaFuncAttributeMaxDynamicSharedMemorySize, SMEM_BYTES);
    }
    Params p;
    for (int br = 0; br < 2; br++) {
        void* const* in = d_in + br * 5;
        CUtensorMap* m = p.maps + br * 5;
        encode(fn, m + 0, in[0], 2, 448, 2432, 1, 1, 896, 0, 0, 0, NQ);
        encode(fn, m + 1, in[1], 5, 64, 8, 128, 128, 512, 128, 4096, 524288, 8);
        encode(fn, m + 2, in[2], 5, 64, 8, 128, 128, 512, 128, 4096, 524288, 8);
        encode(fn, m + 3, in[3], 5, 64, 8, 56, 16, 8192, 128, 65536, 512, 8);
        encode(fn, m + 4, in[4], 5, 448, 8, 8, 16, 896, 8 * 896, 32 * 896, 256 * 896, 8);
    }
    encode(fn, p.maps + 10, d_out, 2, 896, 2432, 1, 1, 1792, 0, 0, 0, 128);
    encode(fn, p.maps + 11, d_out, 2, 896, 2432, 1, 1, 1792, 0, 0, 0, 24);
    p.out = (__nv_bfloat16*)d_out;
    fused_mha_kernel<<<132, 384, SMEM_BYTES>>>(p);
}
```
